```python
import torch

def _softmax(x, axis=-1):
    return torch.softmax(x, dim=axis)

def _gelu(x):
    return torch.nn.functional.gelu(x, approximate='tanh')

def _silu(x):
    return torch.nn.functional.silu(x)

def _sigmoid(x):
    return torch.sigmoid(x)

def _layernorm(x, axis=-1, eps=1e-05):
    m = x.mean(dim=axis, keepdim=True)
    v = x.var(dim=axis, keepdim=True, unbiased=False)
    return (x - m) / torch.sqrt(v + eps)

def _scatter_add(tgt, idx, src, axis=0):
    return tgt.clone().index_add_(axis, idx, src)

def _segment_sum(src, seg, n):
    out = torch.zeros((n,) + src.shape[1:], dtype=src.dtype)
    return out.index_add_(0, seg, src)

def _pad(x, pw):
    flat = tuple((v for pair in reversed(pw) for v in pair))
    return torch.nn.functional.pad(x, flat)
kernel_name = 'adaLN_cond__compressed_kv_cla__dense_activation_relu__decode'

def setup_inputs():

    _w = lambda a: (lambda t: t.to(torch.bfloat16) if t.is_floating_point() else t)(torch.as_tensor(a))

    def _A_setup():
        B, H, Sq, Sk, D, M = (4, 32, 1, 4096, 128, 512)
        Dc = 4 * D
        return {'x': _w((lambda *s: torch.randn(*s, dtype=torch.bfloat16) * 0.05)(B, Sq, M)), 'c_kv': _w((lambda *s: torch.randn(*s, dtype=torch.bfloat16) * 1.6)(B, Sk, Dc)), 'w_q': _w((lambda *s: torch.randn(*s, dtype=torch.bfloat16) * 1.6)(M, H, D) * M ** (-0.5)), 'w_uk': _w((lambda *s: torch.randn(*s, dtype=torch.bfloat16) * 1.6)(Dc, H, D) * Dc ** (-0.5)), 'w_uv': _w((lambda *s: torch.randn(*s, dtype=torch.bfloat16) * 1.6)(Dc, H, D) * Dc ** (-0.5)), 'w_o': _w((lambda *s: torch.randn(*s, dtype=torch.bfloat16) * 1.6)(H, D, M) * (H * D) ** (-0.5))}
    _A_in = _A_setup()

    def _B_setup():
        B, S, D, Dff = (4, 1, 512, 1376)
        return {'x': _w((lambda *s: torch.randn(*s, dtype=torch.bfloat16) * 0.05)(B, S, D)), 'w1': _w((lambda *s: torch.randn(*s, dtype=torch.bfloat16) * 0.05)(D, Dff)), 'w2': _w((lambda *s: torch.randn(*s, dtype=torch.bfloat16) * 0.05)(Dff, D))}
    _B_in = _B_setup()
    return {'A_x': _A_in['x'], 'A_c_kv': _A_in['c_kv'], 'A_w_q': _A_in['w_q'], 'A_w_uk': _A_in['w_uk'], 'A_w_uv': _A_in['w_uv'], 'A_w_o': _A_in['w_o'], 'B_x': _B_in['x'], 'B_w1': _B_in['w1'], 'B_w2': _B_in['w2'], 'c': _w((lambda *s: torch.randn(*s, dtype=torch.bfloat16) * 0.2)(4, 512) * 8.0), 'w_mod': _w((lambda *s: torch.randn(*s, dtype=torch.bfloat16) * 0.2)(512, 6 * 512) * 512 ** (-0.5) * 8.0)}

def reference(A_x, A_c_kv, A_w_q, A_w_uk, A_w_uv, A_w_o, B_x, B_w1, B_w2, c, w_mod):

    def _A_ref(x, c_kv, w_q, w_uk, w_uv, w_o):
        B, Sq, M = (x.shape[0], x.shape[1], x.shape[2])
        Sk = c_kv.shape[1]
        H, D = (w_q.shape[1], w_q.shape[2])
        q = torch.einsum('bqm,mhd->bhqd', x, w_q)
        k = torch.einsum('bkc,chd->bhkd', c_kv, w_uk)
        v = torch.einsum('bkc,chd->bhkd', c_kv, w_uv)
        scores = torch.einsum('bhqd,bhkd->bhqk', q, k) * D ** (-0.5)
        off = Sk - Sq
        qi = torch.arange(Sq)[:, None]
        kj = torch.arange(Sk)[None, :]
        cmask = kj <= qi + off
        scores = torch.where(cmask[None, None], scores, -1000000000.0)
        p = _softmax(scores, axis=-1)
        ctx = torch.einsum('bhqk,bhkd->bhqd', p, v)
        return torch.einsum('bhqd,hdm->bqm', ctx, w_o)

    def _B_ref(x, w1, w2):
        h = torch.einsum('bsd,df->bsf', x, w1)
        zero = torch.zeros_like(h)
        h = torch.maximum(h, zero)
        return torch.einsum('bsf,fd->bsd', h, w2)
    x = A_x
    mod = (_silu(c) @ w_mod).reshape(c.shape[0], 6, 1, -1)
    sa, ca, ga, sb, cb, gb = (mod[:, 0].clone(), mod[:, 1].clone(), mod[:, 2].clone(), mod[:, 3].clone(), mod[:, 4].clone(), mod[:, 5].clone())
    h = _layernorm(x, axis=-1) * (1 + ca) + sa
    x = x + ga * _A_ref(h, A_c_kv, A_w_q, A_w_uk, A_w_uv, A_w_o)
    h = _layernorm(x, axis=-1) * (1 + cb) + sb
    x = x + gb * _B_ref(h, B_w1, B_w2)
    return x
```

```cpp
#include <cuda_runtime.h>
#include <cuda_bf16.h>
#include <cuda.h>
#include <stdint.h>

#define DEVINL __device__ __forceinline__

namespace mla {

constexpr int NCTA = 128;
constexpr int NTHR = 320;
constexpr uint32_t SENT = 0xFFFFFFFFu;
constexpr int SPIN_LIMIT = 1 << 17;

struct __align__(1024) Scratch {
  uint32_t mod[4 * 1536];
  uint32_t qpart[32 * 4 * 4 * 128];
  uint32_t qabs[4 * 2 * 4096];
  uint32_t opart[32 * 4 * 4 * 16 * 64];
  uint32_t stats[32 * 4 * 16 * 2];
  uint32_t ctxp[32 * 4 * 4 * 64];
  uint32_t outp[128 * 32 * 8];
  uint32_t x1[4 * 256];
  uint32_t yp[128 * 88 * 8];
  uint32_t ctr[64];
};
constexpr int FRONT_PK = (4 * 1536 + 32 * 4 * 4 * 128 + 4 * 2 * 4096) / 4 / NCTA;
constexpr int TAIL_WORDS = 32 * 4 * 4 * 16 * 64 + 32 * 4 * 16 * 2 + 32 * 4 * 4 * 64 + 128 * 32 * 8 + 4 * 256 + 128 * 88 * 8;
constexpr int TAIL_PK = TAIL_WORDS / 4 / NCTA;
static_assert(FRONT_PK * 4 * NCTA == 4 * 1536 + 32 * 4 * 4 * 128 + 4 * 2 * 4096, "front split");
static_assert(TAIL_PK * 4 * NCTA == TAIL_WORDS, "tail split");

__device__ Scratch g_scr;

struct Params {
  CUtensorMap ckv;
  CUtensorMap wuk;
  CUtensorMap wuv;
  CUtensorMap wo;
  CUtensorMap w2;
  const __nv_bfloat16 *x, *c, *wq, *wmod, *w1;
  __nv_bfloat16* out;
};

constexpr uint32_t SM_K = 0;
constexpr uint32_t SM_F1 = 131072;
constexpr uint32_t SM_XS = SM_F1;
constexpr uint32_t SM_P = SM_F1 + 16384;
constexpr uint32_t SM_F2 = 163840;
constexpr uint32_t SM_Q = 196608;
constexpr uint32_t SM_MISC = 212992;
constexpr uint32_t SM_BC = SM_MISC;
constexpr uint32_t SM_BH2 = SM_K + 98304;
constexpr uint32_t SM_BA = SM_BC + 4160;
constexpr uint32_t SM_BB = SM_BA + 2176;
constexpr uint32_t SM_RED = SM_BB + 2176;
constexpr uint32_t SM_LN = SM_RED + 2048;
constexpr uint32_t SM_WMAX = SM_LN + 1024;
constexpr uint32_t SM_ALPHA = SM_WMAX + 1024;
constexpr uint32_t SM_LRED = SM_ALPHA + 512;
constexpr uint32_t SM_XMOD = SM_LRED + 512;
constexpr uint32_t SM_BAR = SM_XMOD + 256;
constexpr uint32_t SM_END = SM_BAR + 512;
constexpr uint32_t SMEM_BYTES = SM_END + 1024;
static_assert(SMEM_BYTES <= 232448, "smem");

enum {
  B_KFULL = 0,
  B_WUK = 16, B_WUV, B_WO, B_W2, B_W1,
  B_XS,
  B_XMOD = 25,
  B_PVDONE,
  B_WUKFREE = 30,
  B_GATE, B_S0, B_RST,
  B_COUNT
};

DEVINL uint32_t smem_u32(const void* p) { return (uint32_t)__cvta_generic_to_shared(p); }
DEVINL void mbar_init(uint32_t bar, uint32_t cnt) { asm volatile("mbarrier.init.shared::cta.b64 [%0], %1;" ::"r"(bar), "r"(cnt) : "memory"); }
DEVINL void mbar_expect_tx(uint32_t bar, uint32_t bytes) { asm volatile("mbarrier.arrive.expect_tx.shared::cta.b64 _, [%0], %1;" ::"r"(bar), "r"(bytes) : "memory"); }
DEVINL void mbar_arrive(uint32_t bar) { asm volatile("mbarrier.arrive.shared::cta.b64 _, [%0];" ::"r"(bar) : "memory"); }
DEVINL void flag_err(int code) {
}
DEVINL void mbar_wait(uint32_t bar, uint32_t parity = 0) {
  asm volatile(
      "{\n.reg .pred p;\n.reg .u32 it;\nmov.u32 it, 0;\n"
      "WAIT_%=:\n"
      "mbarrier.try_wait.parity.shared::cta.b64 p, [%0], %1;\n"
      "@p bra DONE_%=;\n"
      "add.u32 it, it, 1;\n"
      "setp.lt.u32 p, it, %2;\n"
      "@p bra WAIT_%=;\n"
      "DONE_%=:\n}"
      ::"r"(bar), "r"(parity), "n"(SPIN_LIMIT) : "memory");
}
DEVINL void mbar_wait_cluster(uint32_t bar, uint32_t parity = 0) {
  asm volatile(
      "{\n.reg .pred p;\n.reg .u32 it;\nmov.u32 it, 0;\n"
      "WAIT_%=:\n"
      "mbarrier.try_wait.parity.acquire.cluster.shared::cta.b64 p, [%0], %1;\n"
      "@p bra DONE_%=;\n"
      "add.u32 it, it, 1;\n"
      "setp.lt.u32 p, it, %2;\n"
      "@p bra WAIT_%=;\n"
      "DONE_%=:\n}"
      ::"r"(bar), "r"(parity), "n"(SPIN_LIMIT) : "memory");
}
DEVINL void tma2d(uint32_t dst, const CUtensorMap* m, int c0, int c1, uint32_t bar) {
  asm volatile("cp.async.bulk.tensor.2d.shared::cluster.global.mbarrier::complete_tx::bytes [%0], [%1, {%3, %4}], [%2];"
               ::"r"(dst), "l"(m), "r"(bar), "r"(c0), "r"(c1) : "memory");
}
DEVINL void cp16(uint32_t dst, const void* src) { asm volatile("cp.async.cg.shared.global [%0], [%1], 16;" ::"r"(dst), "l"(src) : "memory"); }
DEVINL void cp_commit() { asm volatile("cp.async.commit_group;" ::: "memory"); }
template <int N> DEVINL void cp_wait() { asm volatile("cp.async.wait_group %0;" ::"n"(N) : "memory"); }
DEVINL void bar_sync(int id, int n) { asm volatile("bar.sync %0, %1;" ::"r"(id), "r"(n) : "memory"); }
DEVINL void bar_arrive(int id, int n) { asm volatile("bar.arrive %0, %1;" ::"r"(id), "r"(n) : "memory"); }
DEVINL void fence_async_smem() { asm volatile("fence.proxy.async.shared::cta;" ::: "memory"); }

DEVINL uint4 ld_rlx16(const void* p) {
  uint4 v;
  asm volatile("ld.relaxed.gpu.global.v4.u32 {%0,%1,%2,%3}, [%4];" : "=r"(v.x), "=r"(v.y), "=r"(v.z), "=r"(v.w) : "l"(p) : "memory");
  return v;
}
DEVINL uint2 ld_rlx8(const void* p) {
  uint2 v;
  asm volatile("ld.relaxed.gpu.global.v2.u32 {%0,%1}, [%2];" : "=r"(v.x), "=r"(v.y) : "l"(p) : "memory");
  return v;
}
DEVINL uint32_t ld_rlx4(const void* p) {
  uint32_t v;
  asm volatile("ld.relaxed.gpu.global.u32 %0, [%1];" : "=r"(v) : "l"(p) : "memory");
  return v;
}
DEVINL void st_rlx16(void* p, uint4 v) {
  asm volatile("st.relaxed.gpu.global.v4.u32 [%0], {%1,%2,%3,%4};" ::"l"(p), "r"(v.x), "r"(v.y), "r"(v.z), "r"(v.w) : "memory");
}
DEVINL void st_rlx8(void* p, uint2 v) { asm volatile("st.relaxed.gpu.global.v2.u32 [%0], {%1,%2};" ::"l"(p), "r"(v.x), "r"(v.y) : "memory"); }
DEVINL void st_rlx4(void* p, uint32_t v) { asm volatile("st.relaxed.gpu.global.u32 [%0], %1;" ::"l"(p), "r"(v) : "memory"); }
DEVINL uint4 ldg16(const void* p) {
  uint4 v;
  asm volatile("ld.global.nc.v4.u32 {%0,%1,%2,%3}, [%4];" : "=r"(v.x), "=r"(v.y), "=r"(v.z), "=r"(v.w) : "l"(p));
  return v;
}
DEVINL bool ok16(const uint4& v) { return (v.x != SENT) & (v.y != SENT) & (v.z != SENT) & (v.w != SENT); }

template <int N>
DEVINL void poll16(const uint32_t* const (&p)[N], uint4 (&v)[N], int code) {
  int it = 0;
  while (true) {
    bool ok = true;
#pragma unroll
    for (int i = 0; i < N; i++) v[i] = ld_rlx16(p[i]);
#pragma unroll
    for (int i = 0; i < N; i++) ok &= ok16(v[i]);
    if (ok) break;
    if (++it >= SPIN_LIMIT) { flag_err(code); break; }
  }
}
DEVINL uint32_t poll4(const uint32_t* p, int code) {
  uint32_t v;
  int it = 0;
  while ((v = ld_rlx4(p)) == SENT) {
    if (++it >= SPIN_LIMIT) { flag_err(code); break; }
  }
  return v;
}

DEVINL void sts16(uint32_t a, uint4 v) { asm volatile("st.shared.v4.b32 [%0], {%1,%2,%3,%4};" ::"r"(a), "r"(v.x), "r"(v.y), "r"(v.z), "r"(v.w) : "memory"); }
DEVINL void sts8(uint32_t a, uint32_t x, uint32_t y) { asm volatile("st.shared.v2.b32 [%0], {%1,%2};" ::"r"(a), "r"(x), "r"(y) : "memory"); }
DEVINL void sts4(uint32_t a, uint32_t x) { asm volatile("st.shared.b32 [%0], %1;" ::"r"(a), "r"(x) : "memory"); }
DEVINL void sts4f(uint32_t a, float x) { asm volatile("st.shared.f32 [%0], %1;" ::"r"(a), "f"(x) : "memory"); }
DEVINL void sts2(uint32_t a, uint16_t x) { asm volatile("st.shared.b16 [%0], %1;" ::"r"(a), "h"(x) : "memory"); }
DEVINL uint4 lds16(uint32_t a) {
  uint4 v;
  asm volatile("ld.shared.v4.b32 {%0,%1,%2,%3}, [%4];" : "=r"(v.x), "=r"(v.y), "=r"(v.z), "=r"(v.w) : "r"(a) : "memory");
  return v;
}
DEVINL float4 lds16f(uint32_t a) {
  float4 v;
  asm volatile("ld.shared.v4.f32 {%0,%1,%2,%3}, [%4];" : "=f"(v.x), "=f"(v.y), "=f"(v.z), "=f"(v.w) : "r"(a) : "memory");
  return v;
}
DEVINL float2 lds8f(uint32_t a) {
  float2 v;
  asm volatile("ld.shared.v2.f32 {%0,%1}, [%2];" : "=f"(v.x), "=f"(v.y) : "r"(a) : "memory");
  return v;
}
DEVINL float lds4f(uint32_t a) {
  float v;
  asm volatile("ld.shared.f32 %0, [%1];" : "=f"(v) : "r"(a) : "memory");
  return v;
}

DEVINL uint32_t pack_bf16(float lo, float hi) {
  uint32_t r;
  asm("cvt.rn.bf16x2.f32 %0, %1, %2;" : "=r"(r) : "f"(hi), "f"(lo));
  return r;
}
DEVINL float bf_lo(uint32_t w) { return __uint_as_float(w << 16); }
DEVINL float bf_hi(uint32_t w) { return __uint_as_float(w & 0xFFFF0000u); }
DEVINL float bfr(float x) { return __uint_as_float(pack_bf16(x, 0.f) << 16); }
DEVINL float ex2(float x) {
  float y;
  asm("ex2.approx.ftz.f32 %0, %1;" : "=f"(y) : "f"(x));
  return y;
}
DEVINL void unpack8(const uint4& v, float (&f)[8]) {
  f[0] = bf_lo(v.x); f[1] = bf_hi(v.x); f[2] = bf_lo(v.y); f[3] = bf_hi(v.y);
  f[4] = bf_lo(v.z); f[5] = bf_hi(v.z); f[6] = bf_lo(v.w); f[7] = bf_hi(v.w);
}

DEVINL void ldsm4(uint32_t a, uint32_t (&r)[4]) {
  asm volatile("ldmatrix.sync.aligned.m8n8.x4.shared.b16 {%0,%1,%2,%3}, [%4];" : "=r"(r[0]), "=r"(r[1]), "=r"(r[2]), "=r"(r[3]) : "r"(a) : "memory");
}
DEVINL void ldsm4t(uint32_t a, uint32_t (&r)[4]) {
  asm volatile("ldmatrix.sync.aligned.m8n8.x4.trans.shared.b16 {%0,%1,%2,%3}, [%4];" : "=r"(r[0]), "=r"(r[1]), "=r"(r[2]), "=r"(r[3]) : "r"(a) : "memory");
}
DEVINL void ldsm2(uint32_t a, uint32_t& r0, uint32_t& r1) {
  asm volatile("ldmatrix.sync.aligned.m8n8.x2.shared.b16 {%0,%1}, [%2];" : "=r"(r0), "=r"(r1) : "r"(a) : "memory");
}
DEVINL void stsm4t(uint32_t a, uint32_t r0, uint32_t r1, uint32_t r2, uint32_t r3) {
  asm volatile("stmatrix.sync.aligned.m8n8.x4.trans.shared.b16 [%0], {%1,%2,%3,%4};" ::"r"(a), "r"(r0), "r"(r1), "r"(r2), "r"(r3) : "memory");
}
DEVINL void mma16816(float (&d)[4], const uint32_t (&a)[4], uint32_t b0, uint32_t b1) {
  asm volatile("mma.sync.aligned.m16n8k16.row.col.f32.bf16.bf16.f32 {%0,%1,%2,%3}, {%4,%5,%6,%7}, {%8,%9}, {%0,%1,%2,%3};"
               : "+f"(d[0]), "+f"(d[1]), "+f"(d[2]), "+f"(d[3])
               : "r"(a[0]), "r"(a[1]), "r"(a[2]), "r"(a[3]), "r"(b0), "r"(b1));
}
DEVINL uint64_t gdesc(uint32_t addr) {
  return (uint64_t)((addr & 0x3FFFF) >> 4) | (1ull << 16) | (64ull << 32) | (1ull << 62);
}
template <int TA>
DEVINL void wgmma_n32(float (&d)[16], uint64_t da, uint64_t db, int scale_d) {
  asm volatile(
      "{\n.reg .pred p;\nsetp.ne.b32 p, %18, 0;\n"
      "wgmma.mma_async.sync.aligned.m64n32k16.f32.bf16.bf16 "
      "{%0,%1,%2,%3,%4,%5,%6,%7,%8,%9,%10,%11,%12,%13,%14,%15}, %16, %17, p, 1, 1, %19, 0;\n}\n"
      : "+f"(d[0]), "+f"(d[1]), "+f"(d[2]), "+f"(d[3]), "+f"(d[4]), "+f"(d[5]), "+f"(d[6]), "+f"(d[7]),
        "+f"(d[8]), "+f"(d[9]), "+f"(d[10]), "+f"(d[11]), "+f"(d[12]), "+f"(d[13]), "+f"(d[14]), "+f"(d[15])
      : "l"(da), "l"(db), "r"(scale_d), "n"(TA));
}
DEVINL void wg_fence() { asm volatile("wgmma.fence.sync.aligned;" ::: "memory"); }
DEVINL void wg_commit() { asm volatile("wgmma.commit_group.sync.aligned;" ::: "memory"); }
DEVINL void wg_wait0() { asm volatile("wgmma.wait_group.sync.aligned 0;" ::: "memory"); }

template <bool TRANS, bool DUP>
DEVINL void gemv128(float (&o)[4], uint32_t tile, uint32_t bs, int warp, int lane) {
  float a0[4] = {0.f, 0.f, 0.f, 0.f}, a1[4] = {0.f, 0.f, 0.f, 0.f};
  const uint32_t brow = bs + (DUP ? (lane & 3) : (lane & 7)) * 272 + (lane >> 3) * 16;
  uint32_t abase;
  if (TRANS) {
    const int ro = (lane & 7) + 8 * (lane >> 4);
    const int ch = 2 * (warp & 3) + ((lane >> 3) & 1);
    abase = tile + (warp >> 2) * 16384 + ro * 128 + ((ch ^ (lane & 7)) << 4);
  } else {
    abase = tile + (16 * warp + (lane & 7) + 8 * ((lane >> 3) & 1)) * 128;
  }
#pragma unroll
  for (int kp = 0; kp < 4; kp++) {
    uint32_t b[4], fa[4], fb[4];
    ldsm4(brow + kp * 64, b);
    if (TRANS) {
      ldsm4t(abase + (2 * kp) * 2048, fa);
      ldsm4t(abase + (2 * kp + 1) * 2048, fb);
    } else {
      const int k0 = 2 * kp, k1 = 2 * kp + 1;
      ldsm4(abase + (k0 >> 2) * 16384 + (((2 * (k0 & 3) + (lane >> 4)) ^ (lane & 7)) << 4), fa);
      ldsm4(abase + (k1 >> 2) * 16384 + (((2 * (k1 & 3) + (lane >> 4)) ^ (lane & 7)) << 4), fb);
    }
    mma16816(a0, fa, b[0], b[1]);
    mma16816(a1, fb, b[2], b[3]);
  }
#pragma unroll
  for (int i = 0; i < 4; i++) o[i] = a0[i] + a1[i];
}

template <int NKP>
DEVINL void gemv_narrow(float (&o)[4], uint32_t tile  , uint32_t bs  , int lane) {
  float a0[4] = {0.f, 0.f, 0.f, 0.f}, a1[4] = {0.f, 0.f, 0.f, 0.f};
  const uint32_t brow = bs + (lane & 3) * 1040 + (lane >> 3) * 16;
  const int ro = (lane & 7) + 8 * (lane >> 4);
  const uint32_t abase = tile + ro * 32 + (((((lane >> 3) & 1)) ^ ((ro >> 2) & 1)) << 4);
#pragma unroll
  for (int kp = 0; kp < NKP; kp++) {
    uint32_t b[4], fa[4], fb[4];
    ldsm4(brow + kp * 64, b);
    ldsm4t(abase + (2 * kp) * 512, fa);
    ldsm4t(abase + (2 * kp + 1) * 512, fb);
    mma16816(a0, fa, b[0], b[1]);
    mma16816(a1, fb, b[2], b[3]);
  }
#pragma unroll
  for (int i = 0; i < 4; i++) o[i] = a0[i] + a1[i];
}

DEVINL float colsum16(float (&v)[16], int lane) {
  const bool h4 = lane & 16, h3 = lane & 8, h2 = lane & 4, h1 = lane & 2;
  float a[8], b[4], c[2];
#pragma unroll
  for (int i = 0; i < 8; i++) {
    float keep = h4 ? v[i + 8] : v[i], send = h4 ? v[i] : v[i + 8];
    a[i] = keep + __shfl_xor_sync(0xffffffffu, send, 16);
  }
#pragma unroll
  for (int i = 0; i < 4; i++) {
    float keep = h3 ? a[i + 4] : a[i], send = h3 ? a[i] : a[i + 4];
    b[i] = keep + __shfl_xor_sync(0xffffffffu, send, 8);
  }
#pragma unroll
  for (int i = 0; i < 2; i++) {
    float keep = h2 ? b[i + 2] : b[i], send = h2 ? b[i] : b[i + 2];
    c[i] = keep + __shfl_xor_sync(0xffffffffu, send, 4);
  }
  float keep = h1 ? c[1] : c[0], send = h1 ? c[0] : c[1];
  float d = keep + __shfl_xor_sync(0xffffffffu, send, 2);
  return d + __shfl_xor_sync(0xffffffffu, d, 1);
}

DEVINL void ln_row(const float (&v)[16], float (&o)[16]) {
  float s = 0.f;
#pragma unroll
  for (int i = 0; i < 16; i++) s += v[i];
  float mean = s * (1.f / 16.f), m2 = 0.f;
#pragma unroll
  for (int i = 0; i < 16; i++) { float d = v[i] - mean; m2 = fmaf(d, d, m2); }
  float n = 16.f;
#pragma unroll
  for (int o_ = 1; o_ < 32; o_ <<= 1) {
    float mo = __shfl_xor_sync(0xffffffffu, mean, o_);
    float so = __shfl_xor_sync(0xffffffffu, m2, o_);
    float d = mo - mean;
    m2 = m2 + so + d * d * (n * 0.5f);
    mean = 0.5f * (mean + mo);
    n *= 2.f;
  }
  const float mb = bfr(mean);
  const float vb = bfr(m2 * (1.f / 512.f));
  const float den = bfr(sqrtf(bfr(vb + 1e-5f)));
#pragma unroll
  for (int i = 0; i < 16; i++) o[i] = bfr(__fdiv_rn(bfr(v[i] - mb), den));
}

#define STAMP(i)
#define STAMP_T(i, t)

#define MLA_WINDOW 6

__global__ void __cluster_dims__(2, 1, 1) __launch_bounds__(NTHR, 1)
decode_kernel(const __grid_constant__ Params P) {
  extern __shared__ uint8_t smem_raw[];
  const uint32_t sb = (smem_u32(smem_raw) + 1023u) & ~1023u;
  const int tid = threadIdx.x, warp = tid >> 5, lane = tid & 31;
  const int j = blockIdx.x;
  const int r = j & 1;
  const int hd = j >> 2, qr = j & 3;
  const int ab = j >> 5, as = (j & 31) >> 1;
  Scratch* const S = &g_scr;
  const uint32_t bar0 = sb + SM_BAR;
#define BAR(i) (bar0 + 8u * (i))

  uint4 c_raw, x_raw0, x_raw1;
  if (warp < 8) {
    const int p = j >> 1;
#pragma unroll
    for (int i = 0; i < 2; i++) {
      const int q = i * 256 + tid, row = q >> 1, ch = q & 1;
      cp16(sb + SM_Q + row * 32 + ((ch ^ ((row >> 2) & 1)) << 4), P.wmod + (size_t)(256 * r + row) * 3072 + 16 * p + 8 * ch);
    }
    cp_commit();
    c_raw = ldg16(P.c + tid * 8);
    if (warp < 4) {
      x_raw0 = ldg16(P.x + warp * 512 + lane * 16);
      x_raw1 = ldg16(P.x + warp * 512 + lane * 16 + 8);
    }
#pragma unroll
    for (int i = 0; i < 8; i++) {
      const int q = i * 256 + tid, row = q >> 4, ch = q & 15;
      cp16(sb + SM_F1 + (ch >> 3) * 16384 + row * 128 + (((ch & 7) ^ (row & 7)) << 4),
           P.wq + (size_t)(128 * qr + row) * 4096 + hd * 128 + ch * 8);
    }
    cp_commit();
  } else if (warp == 8) {
    if (lane == 0) {
      for (int i = 0; i < 16; i++) mbar_init(BAR(B_KFULL + i), 1);
      mbar_init(BAR(B_WUK), 1); mbar_init(BAR(B_WUV), 1); mbar_init(BAR(B_WO), 1); mbar_init(BAR(B_W2), 1);
      mbar_init(BAR(B_W1), 32);
      for (int i = 0; i < 4; i++) { mbar_init(BAR(B_XS + i), 1); mbar_init(BAR(B_PVDONE + i), 4); }
      mbar_init(BAR(B_XMOD), 1);
      mbar_init(BAR(B_WUKFREE), 8); mbar_init(BAR(B_GATE), 1); mbar_init(BAR(B_S0), 1); mbar_init(BAR(B_RST), 1);
      asm volatile("fence.mbarrier_init.release.cluster;" ::: "memory");
      fence_async_smem();
      for (int i = 0; i < 4; i++) mbar_expect_tx(BAR(B_XS + i), 8192);
      mbar_expect_tx(BAR(B_XMOD), 256);
    }
    __syncwarp();
  }
  asm volatile("barrier.cluster.arrive.release.aligned;\nbarrier.cluster.wait.acquire.aligned;" ::: "memory");

  if (warp == 8) {
    if (lane == 0) {
      asm volatile("prefetch.tensormap [%0];" ::"l"(&P.wuk) : "memory");
      asm volatile("prefetch.tensormap [%0];" ::"l"(&P.ckv) : "memory");
      asm volatile("prefetch.tensormap [%0];" ::"l"(&P.wuv) : "memory");
      asm volatile("prefetch.tensormap [%0];" ::"l"(&P.wo) : "memory");
      asm volatile("prefetch.tensormap [%0];" ::"l"(&P.w2) : "memory");
      mbar_wait(BAR(B_GATE));
      STAMP(20);
      mbar_expect_tx(BAR(B_WUK), 32768);
#pragma unroll
      for (int s = 0; s < 4; s++)
        tma2d(sb + SM_F2 + (s & 1) * 16384 + (s >> 1) * 8192, &P.wuk, hd * 128 + (s & 1) * 64, qr * 128 + (s >> 1) * 64, BAR(B_WUK));
      constexpr int W0 = MLA_WINDOW - 4 > 0 ? MLA_WINDOW - 4 : 0;
      auto issue_k = [&](int i) {
        mbar_expect_tx(BAR(B_KFULL + i), 8192);
        tma2d(sb + SM_K + i * 8192, &P.ckv, r * 256 + (i & 3) * 64, ab * 4096 + as * 256 + (i >> 2) * 64, BAR(B_KFULL + i));
      };
#pragma unroll
      for (int i = 0; i < W0; i++) issue_k(i);
      mbar_wait(BAR(B_WUK));
#pragma unroll
      for (int i = W0; i < MLA_WINDOW; i++) issue_k(i);
#pragma unroll
      for (int i = 0; i < 16; i++) {
        mbar_wait(BAR(B_KFULL + i));
        if (i + MLA_WINDOW < 16) issue_k(i + MLA_WINDOW);
      }
      STAMP(21);
      mbar_wait(BAR(B_PVDONE + 0));
      mbar_expect_tx(BAR(B_WUV), 32768);
#pragma unroll
      for (int s = 0; s < 8; s++)
        tma2d(sb + SM_K + (s >> 2) * 16384 + (s & 3) * 4096, &P.wuv, hd * 128 + (s >> 2) * 64,
              256 * (qr >> 1) + 64 * (s & 3) + 32 * (qr & 1), BAR(B_WUV));
      mbar_wait(BAR(B_PVDONE + 1));
      mbar_expect_tx(BAR(B_WO), 32768);
#pragma unroll
      for (int s = 0; s < 4; s++)
        tma2d(sb + SM_K + 32768 + (s & 1) * 16384 + (s >> 1) * 8192, &P.wo, qr * 128 + (s & 1) * 64, hd * 128 + (s >> 1) * 64, BAR(B_WO));
    }
    __syncwarp();
    if (j < 86) {
      mbar_wait(BAR(B_WUV));
      mbar_wait(BAR(B_WUKFREE));
#pragma unroll 4
      for (int i = 0; i < 32; i++) {
        const int q = i * 32 + lane, row = q >> 1, ch = q & 1;
        cp16(sb + SM_F2 + 16384 + row * 32 + ((ch ^ ((row >> 2) & 1)) << 4), P.w1 + (size_t)row * 1376 + 16 * j + 8 * ch);
      }
      asm volatile("cp.async.mbarrier.arrive.noinc.shared::cta.b64 [%0];" ::"r"(BAR(B_W1)) : "memory");
      if (lane == 0) {
        mbar_wait(BAR(B_PVDONE + 2));
        mbar_expect_tx(BAR(B_W2), 16384);
#pragma unroll
        for (int s = 0; s < 8; s++) tma2d(sb + SM_K + 65536 + s * 2048, &P.w2, s * 64, 16 * j, BAR(B_W2));
      }
    }
  } else if (warp == 9) {
    {
      uint4* fp = reinterpret_cast<uint4*>(S->mod) + j * FRONT_PK;
      const uint4 sv = make_uint4(SENT, SENT, SENT, SENT);
      for (int i = lane; i < FRONT_PK; i += 32) fp[i] = sv;
      __threadfence();
      __syncwarp();
      if (lane == 0) {
        uint32_t old;
        asm volatile("atom.add.release.gpu.global.u32 %0, [%1], 1;" : "=r"(old) : "l"(S->ctr) : "memory");
        const uint32_t target = (old & ~(uint32_t)(NCTA - 1)) + NCTA;
        int it = 0;
        uint32_t v;
        do {
          asm volatile("ld.acquire.gpu.global.u32 %0, [%1];" : "=r"(v) : "l"(S->ctr) : "memory");
        } while ((int)(v - target) < 0 && ++it < SPIN_LIMIT);
        if (it >= SPIN_LIMIT) flag_err(1);
        mbar_arrive(BAR(B_S0));
        STAMP(22);
      }
      __syncwarp();
      uint4* tp = reinterpret_cast<uint4*>(S->opart) + j * TAIL_PK;
#pragma unroll 6
      for (int i = lane; i < TAIL_PK; i += 32) tp[i] = sv;
      __threadfence();
      __syncwarp();
      if (lane == 0) { mbar_arrive(BAR(B_RST)); STAMP(23); }
    }
    mbar_wait(BAR(B_WUKFREE));
    mbar_wait(BAR(B_KFULL + 15));
#pragma unroll 4
    for (int i = 0; i < 32; i++) {
      const int q = i * 32 + lane, row = q >> 1, ch = q & 1;
      cp16(sb + SM_F2 + row * 32 + ((ch ^ ((row >> 2) & 1)) << 4), P.wmod + (size_t)row * 3072 + 1024 + 16 * j + 8 * ch);
    }
    cp_commit();
    const int mg = j & 31;
    const int mcol = 16 * mg + ((lane >> 4) & 1) * 8 + ((lane >> 3) & 1) * 4 + ((lane >> 2) & 1) * 2 + ((lane >> 1) & 1);
    const float xv = __bfloat162float(P.x[ab * 512 + mcol]);
    cp_wait<0>();
    __syncwarp();
    {
      float o[4];
      gemv_narrow<16>(o, sb + SM_F2, sb + SM_BC, lane);
      const int g = lane >> 2, t = lane & 3;
      const float v0 = (t >> 1) ? o[2] : o[0], v1 = (t >> 1) ? o[3] : o[1];
      const float send = (g & 1) ? v0 : v1;
      const float recv = __shfl_xor_sync(0xffffffffu, send, 4);
      const uint32_t w = (g & 1) ? pack_bf16(recv, v1) : pack_bf16(v0, recv);
      const int b = 2 * (t & 1) + (g & 1), row = (g + 8 * (t >> 1)) & ~1;
      st_rlx4(S->mod + b * 1536 + (1024 + 16 * j + row) / 2, w);
    }
    STAMP(24);
    const uint32_t gaw = poll4(S->mod + ab * 1536 + (1024 + mcol) / 2, 20);
    const uint32_t gbw = poll4(S->mod + ab * 1536 + (2560 + mcol) / 2, 21);
    const float ga = (mcol & 1) ? bf_hi(gaw) : bf_lo(gaw), gb = (mcol & 1) ? bf_hi(gbw) : bf_lo(gbw);
    float x1v;
    {
      const uint32_t* pp[2] = {S->outp + (j * 32 + lane) * 8, S->outp + (j * 32 + lane) * 8 + 4};
      uint4 v[2];
      poll16<2>(pp, v, 22);
      float f[16], t8[8];
      unpack8(v[0], t8);
#pragma unroll
      for (int i = 0; i < 8; i++) f[i] = t8[i];
      unpack8(v[1], t8);
#pragma unroll
      for (int i = 0; i < 8; i++) f[8 + i] = t8[i];
      const float o = colsum16(f, lane);
      x1v = bfr(xv + bfr(ga * bfr(o)));
      const float nb = __shfl_xor_sync(0xffffffffu, x1v, 2);
      if ((lane & 3) == 0) st_rlx4(S->x1 + ab * 256 + mcol / 2, pack_bf16(x1v, nb));
      STAMP(25);
    }
    {
      float f[16];
#pragma unroll
      for (int i = 0; i < 16; i++) f[i] = 0.f;
      const uint32_t* base = S->yp + (size_t)j * 88 * 8;
      const int p2 = lane + 64 < 86 ? lane + 64 : lane;
      const uint32_t* pp[6] = {base + lane * 8, base + lane * 8 + 4, base + (lane + 32) * 8, base + (lane + 32) * 8 + 4,
                               base + p2 * 8, base + p2 * 8 + 4};
      uint4 v[6];
      poll16<6>(pp, v, 23);
      const float w3 = lane + 64 < 86 ? 1.f : 0.f;
      float t8[8];
#pragma unroll
      for (int q = 0; q < 6; q++) {
        unpack8(v[q], t8);
#pragma unroll
        for (int i = 0; i < 8; i++) f[(q & 1) * 8 + i] += (q >= 4) ? (w3 != 0.f ? t8[i] : 0.f) : t8[i];
      }
      const float y = colsum16(f, lane);
      const float o = bfr(x1v + bfr(gb * bfr(y)));
      const float nb = __shfl_xor_sync(0xffffffffu, o, 2);
      if ((lane & 3) == 0) reinterpret_cast<uint32_t*>(P.out)[ab * 256 + mcol / 2] = pack_bf16(o, nb);
      STAMP(26);
    }
  } else {
    const int g = lane >> 2, t = lane & 3;
    {
      float f[8];
      unpack8(c_raw, f);
#pragma unroll
      for (int i = 0; i < 8; i++) f[i] = __fdividef(f[i], 1.f + __expf(-f[i]));
      uint4 w = make_uint4(pack_bf16(f[0], f[1]), pack_bf16(f[2], f[3]), pack_bf16(f[4], f[5]), pack_bf16(f[6], f[7]));
      sts16(sb + SM_BC + (tid >> 6) * 1040 + (tid & 63) * 16, w);
      if (warp < 4) {
        float v[16], o[16], t8[8];
        unpack8(x_raw0, t8);
#pragma unroll
        for (int i = 0; i < 8; i++) v[i] = t8[i];
        unpack8(x_raw1, t8);
#pragma unroll
        for (int i = 0; i < 8; i++) v[8 + i] = t8[i];
        ln_row(v, o);
        if ((lane >> 3) == qr) {
          const uint32_t a = sb + SM_LN + warp * 256 + (lane & 7) * 32;
          sts16(a, make_uint4(pack_bf16(o[0], o[1]), pack_bf16(o[2], o[3]), pack_bf16(o[4], o[5]), pack_bf16(o[6], o[7])));
          sts16(a + 16, make_uint4(pack_bf16(o[8], o[9]), pack_bf16(o[10], o[11]), pack_bf16(o[12], o[13]), pack_bf16(o[14], o[15])));
        }
      }
    }
    cp_wait<1>();
    bar_sync(1, 256);
    if (tid == 0) mbar_arrive(BAR(B_GATE));
    STAMP_T(0, 0);
    {
      float o[4];
      gemv_narrow<1>(o, sb + SM_Q + warp * 32 * 32, sb + SM_BC + (256 * r + 32 * warp) * 2, lane);
      const int row = g + 8 * (t >> 1), b0 = 2 * (t & 1);
      sts4f(sb + SM_RED + warp * 256 + (b0 * 16 + row) * 4, (t >> 1) ? o[2] : o[0]);
      sts4f(sb + SM_RED + warp * 256 + ((b0 + 1) * 16 + row) * 4, (t >> 1) ? o[3] : o[1]);
    }
    bar_sync(1, 256);
    if (tid < 64) {
      float s = 0.f;
#pragma unroll
      for (int w = 0; w < 8; w++) s += lds4f(sb + SM_RED + w * 256 + tid * 4);
      if (r == 1) {
        uint32_t ra, rb;
        asm volatile("mapa.shared::cluster.u32 %0, %1, %2;" : "=r"(ra) : "r"(sb + SM_XMOD + tid * 4), "r"(0));
        asm volatile("mapa.shared::cluster.u32 %0, %1, %2;" : "=r"(rb) : "r"(BAR(B_XMOD)), "r"(0));
        asm volatile("st.async.weak.shared::cluster.mbarrier::complete_tx::bytes.b32 [%0], %1, [%2];" ::"r"(ra), "r"(__float_as_uint(s)), "r"(rb) : "memory");
      } else {
        mbar_wait_cluster(BAR(B_XMOD));
        s += lds4f(sb + SM_XMOD + tid * 4);
        const float nb = __shfl_xor_sync(0xffffffffu, s, 1);
        mbar_wait(BAR(B_S0));
        if ((tid & 1) == 0) st_rlx4(S->mod + (tid >> 4) * 1536 + (16 * (j >> 1) + (tid & 15)) / 2, pack_bf16(s, nb));
      }
      STAMP_T(1, 0);
      mbar_wait(BAR(B_S0));
      const int b = tid >> 4, ch = tid & 15;
      const uint32_t* pp[2] = {S->mod + b * 1536 + (128 * qr + 8 * ch) / 2, S->mod + b * 1536 + (512 + 128 * qr + 8 * ch) / 2};
      uint4 v[2];
      poll16<2>(pp, v, 2);
      float sa[8], ca[8], ln[8];
      unpack8(v[0], sa);
      unpack8(v[1], ca);
      unpack8(lds16(sb + SM_LN + b * 256 + ch * 16), ln);
      float hh[8];
#pragma unroll
      for (int i = 0; i < 8; i++) hh[i] = bfr(ln[i] * bfr(1.f + ca[i])) + sa[i];
      sts16(sb + SM_BA + b * 272 + ch * 16,
            make_uint4(pack_bf16(hh[0], hh[1]), pack_bf16(hh[2], hh[3]), pack_bf16(hh[4], hh[5]), pack_bf16(hh[6], hh[7])));
      STAMP_T(2, 0);
    }
    cp_wait<0>();
    bar_sync(1, 256);
    STAMP_T(3, 0);
    {
      float o[4];
      gemv128<true, true>(o, sb + SM_F1, sb + SM_BA, warp, lane);
      const int d = 16 * warp + g + 8 * (t >> 1), b0 = 2 * (t & 1);
      uint32_t* dst = S->qpart + ((hd * 4 + qr) * 4 + b0) * 128 + d;
      st_rlx4(dst, __float_as_uint((t >> 1) ? o[2] : o[0]));
      st_rlx4(dst + 128, __float_as_uint((t >> 1) ? o[3] : o[1]));
    }
    STAMP_T(4, 0);
    if (tid < 128) {
      const int b = tid >> 5, ch = tid & 31;
      const uint32_t* base = S->qpart + (hd * 16 + b) * 128 + ch * 4;
      const uint32_t* pp[4] = {base, base + 512, base + 1024, base + 1536};
      uint4 v[4];
      poll16<4>(pp, v, 3);
      float q[4];
      q[0] = (__uint_as_float(v[0].x) + __uint_as_float(v[1].x)) + (__uint_as_float(v[2].x) + __uint_as_float(v[3].x));
      q[1] = (__uint_as_float(v[0].y) + __uint_as_float(v[1].y)) + (__uint_as_float(v[2].y) + __uint_as_float(v[3].y));
      q[2] = (__uint_as_float(v[0].z) + __uint_as_float(v[1].z)) + (__uint_as_float(v[2].z) + __uint_as_float(v[3].z));
      q[3] = (__uint_as_float(v[0].w) + __uint_as_float(v[1].w)) + (__uint_as_float(v[2].w) + __uint_as_float(v[3].w));
      sts8(sb + SM_BB + b * 272 + ch * 8, pack_bf16(q[0], q[1]), pack_bf16(q[2], q[3]));
    }
    STAMP_T(5, 0);
    mbar_wait(BAR(B_WUK));
    bar_sync(1, 256);
    STAMP_T(6, 0);
    {
      float o[4];
      gemv128<false, true>(o, sb + SM_F2, sb + SM_BB, warp, lane);
      if (lane == 0) mbar_arrive(BAR(B_WUKFREE));
      const float v0 = (t >> 1) ? o[2] : o[0], v1 = (t >> 1) ? o[3] : o[1];
      const float send = (g & 1) ? v0 : v1;
      const float recv = __shfl_xor_sync(0xffffffffu, send, 4);
      const uint32_t w = (g & 1) ? pack_bf16(recv, v1) : pack_bf16(v0, recv);
      const int b = 2 * (t & 1) + (g & 1);
      const int cl = 128 * (qr & 1) + 16 * warp + ((g + 8 * (t >> 1)) & ~1);
      const int box = cl >> 6, col = cl & 63;
      mbar_wait(BAR(B_RST));
      st_rlx4(S->qabs + (b * 2 + (qr >> 1)) * 4096 + box * 1024 + hd * 32 + (((col >> 3) ^ (hd & 7)) << 2) + ((col & 7) >> 1), w);
    }
    STAMP_T(7, 0);
    {
      const uint32_t* base = S->qabs + (ab * 2 + r) * 4096 + tid * 4;
      const uint32_t* pp[4] = {base, base + 1024, base + 2048, base + 3072};
      uint4 v[4];
      poll16<4>(pp, v, 4);
#pragma unroll
      for (int i = 0; i < 4; i++) sts16(sb + SM_Q + i * 4096 + tid * 16, v[i]);
      fence_async_smem();
    }
    bar_sync(1, 256);
    STAMP_T(8, 0);

    if (warp < 4) {
      uint32_t rslot, rbar;
      asm volatile("mapa.shared::cluster.u32 %0, %1, %2;" : "=r"(rslot) : "r"(sb + SM_XS + tid * 16), "r"(r ^ 1));
      asm volatile("mapa.shared::cluster.u32 %0, %1, %2;" : "=r"(rbar) : "r"(BAR(B_XS)), "r"(r ^ 1));
      float mrun[8], lrun[8];
#pragma unroll
      for (int i = 0; i < 8; i++) { mrun[i] = -INFINITY; lrun[i] = 0.f; }
      constexpr float LOG2E = 1.4426950408889634f;
#pragma unroll 1
      for (int tt = 0; tt < 4; tt++) {
        float s[16];
#pragma unroll
        for (int i = 0; i < 16; i++) s[i] = 0.f;
#pragma unroll
        for (int x = 0; x < 4; x++) {
          mbar_wait(BAR(B_KFULL + tt * 4 + x));
          const uint64_t da = gdesc(sb + SM_K + tt * 32768 + x * 8192), db = gdesc(sb + SM_Q + x * 4096);
          wg_fence();
#pragma unroll
          for (int kk = 0; kk < 4; kk++) wgmma_n32<0>(s, da + kk * 2, db + kk * 2, (x | kk) != 0);
          wg_commit();
        }
        wg_wait0();
        if (tt == 3) STAMP_T(9, 0);
        const uint32_t so = (tt & 1) * 8192;
#pragma unroll
        for (int i = 0; i < 4; i++)
          asm volatile("st.async.weak.shared::cluster.mbarrier::complete_tx::bytes.v4.b32 [%0], {%1,%2,%3,%4}, [%5];"
                       ::"r"(rslot + so + i * 2048), "r"(__float_as_uint(s[4 * i])), "r"(__float_as_uint(s[4 * i + 1])),
                         "r"(__float_as_uint(s[4 * i + 2])), "r"(__float_as_uint(s[4 * i + 3])), "r"(rbar + tt * 8) : "memory");
        mbar_wait_cluster(BAR(B_XS + tt));
#pragma unroll
        for (int i = 0; i < 4; i++) {
          const float4 v = lds16f(sb + SM_XS + so + i * 2048 + tid * 16);
          s[4 * i] = bfr(bfr(s[4 * i] + v.x) * 0.08838834764831845f);
          s[4 * i + 1] = bfr(bfr(s[4 * i + 1] + v.y) * 0.08838834764831845f);
          s[4 * i + 2] = bfr(bfr(s[4 * i + 2] + v.z) * 0.08838834764831845f);
          s[4 * i + 3] = bfr(bfr(s[4 * i + 3] + v.w) * 0.08838834764831845f);
        }
        if (tt == 3) STAMP_T(10, 0);
        {
          float a[8], b4[4], c2[2];
#pragma unroll
          for (int jj = 0; jj < 4; jj++) { a[2 * jj] = fmaxf(s[4 * jj], s[4 * jj + 2]); a[2 * jj + 1] = fmaxf(s[4 * jj + 1], s[4 * jj + 3]); }
          const bool h4 = lane & 16, h3 = lane & 8, h2 = lane & 4;
#pragma unroll
          for (int i = 0; i < 4; i++) {
            float keep = h4 ? a[i + 4] : a[i], send = h4 ? a[i] : a[i + 4];
            b4[i] = fmaxf(keep, __shfl_xor_sync(0xffffffffu, send, 16));
          }
#pragma unroll
          for (int i = 0; i < 2; i++) {
            float keep = h3 ? b4[i + 2] : b4[i], send = h3 ? b4[i] : b4[i + 2];
            c2[i] = fmaxf(keep, __shfl_xor_sync(0xffffffffu, send, 8));
          }
          float keep = h2 ? c2[1] : c2[0], send = h2 ? c2[0] : c2[1];
          const float mx = fmaxf(keep, __shfl_xor_sync(0xffffffffu, send, 4));
          const int col = 8 * (2 * (lane >> 4) + ((lane >> 3) & 1)) + 2 * t + ((lane >> 2) & 1);
          sts4f(sb + SM_WMAX + (tt & 1) * 512 + col * 16 + warp * 4, mx);
        }
        bar_sync(2, 128);
        float al[8];
#pragma unroll
        for (int jj = 0; jj < 4; jj++) {
#pragma unroll
          for (int e = 0; e < 2; e++) {
            const float4 v = lds16f(sb + SM_WMAX + (tt & 1) * 512 + (8 * jj + 2 * t + e) * 16);
            const float mn = fmaxf(fmaxf(fmaxf(v.x, v.y), fmaxf(v.z, v.w)), mrun[2 * jj + e]);
            al[2 * jj + e] = ex2((mrun[2 * jj + e] - mn) * LOG2E);
            mrun[2 * jj + e] = mn;
          }
        }
        uint32_t pk[8];
#pragma unroll
        for (int jj = 0; jj < 4; jj++) {
          const float p00 = ex2((s[4 * jj] - mrun[2 * jj]) * LOG2E), p01 = ex2((s[4 * jj + 1] - mrun[2 * jj + 1]) * LOG2E);
          const float p10 = ex2((s[4 * jj + 2] - mrun[2 * jj]) * LOG2E), p11 = ex2((s[4 * jj + 3] - mrun[2 * jj + 1]) * LOG2E);
          lrun[2 * jj] = fmaf(lrun[2 * jj], al[2 * jj], p00 + p10);
          lrun[2 * jj + 1] = fmaf(lrun[2 * jj + 1], al[2 * jj + 1], p01 + p11);
          pk[2 * jj] = pack_bf16(p00, p01);
          pk[2 * jj + 1] = pack_bf16(p10, p11);
        }
        {
          const int q = lane >> 3, rr = lane & 7;
          const uint32_t pb = sb + SM_P + tt * 4096 + ((q >> 1) * 8 + rr) * 128 + (((2 * warp + (q & 1)) ^ rr) << 4);
          stsm4t(pb, pk[0], pk[1], pk[2], pk[3]);
          stsm4t(pb + 2048, pk[4], pk[5], pk[6], pk[7]);
          if (warp == 0 && g == 0) {
#pragma unroll
            for (int jj = 0; jj < 4; jj++) {
              sts4f(sb + SM_ALPHA + tt * 128 + (8 * jj + 2 * t) * 4, al[2 * jj]);
              sts4f(sb + SM_ALPHA + tt * 128 + (8 * jj + 2 * t + 1) * 4, al[2 * jj + 1]);
            }
          }
        }
        fence_async_smem();
        bar_arrive(3 + tt, 256);
        if (tt == 3) STAMP_T(11, 0);
      }
      {
        float b4[4], c2[2];
        const bool h4 = lane & 16, h3 = lane & 8, h2 = lane & 4;
#pragma unroll
        for (int i = 0; i < 4; i++) {
          float keep = h4 ? lrun[i + 4] : lrun[i], send = h4 ? lrun[i] : lrun[i + 4];
          b4[i] = keep + __shfl_xor_sync(0xffffffffu, send, 16);
        }
#pragma unroll
        for (int i = 0; i < 2; i++) {
          float keep = h3 ? b4[i + 2] : b4[i], send = h3 ? b4[i] : b4[i + 2];
          c2[i] = keep + __shfl_xor_sync(0xffffffffu, send, 8);
        }
        float keep = h2 ? c2[1] : c2[0], send = h2 ? c2[0] : c2[1];
        const float ls = keep + __shfl_xor_sync(0xffffffffu, send, 4);
        const int col = 8 * (2 * (lane >> 4) + ((lane >> 3) & 1)) + 2 * t + ((lane >> 2) & 1);
        sts4f(sb + SM_LRED + col * 16 + warp * 4, ls);
        float mcol = mrun[0];
        const int ci = 2 * (2 * (lane >> 4) + ((lane >> 3) & 1)) + ((lane >> 2) & 1);
#pragma unroll
        for (int i = 1; i < 8; i++) mcol = (ci == i) ? mrun[i] : mcol;
        bar_sync(2, 128);
        if (warp == 0 && r == 0) {
          const float4 v = lds16f(sb + SM_LRED + col * 16);
          const float l = (v.x + v.y) + (v.z + v.w);
          st_rlx8(S->stats + ((col * 4 + ab) * 16 + as) * 2, make_uint2(__float_as_uint(mcol), __float_as_uint(l)));
        }
      }
    } else {
      float o[4][16];
      const int w = warp - 4;
#pragma unroll 1
      for (int tt = 0; tt < 4; tt++) {
        bar_sync(3 + tt, 256);
        if (tt > 0) {
#pragma unroll
          for (int jj = 0; jj < 4; jj++) {
            const float2 a = lds8f(sb + SM_ALPHA + tt * 128 + (8 * jj + 2 * t) * 4);
#pragma unroll
            for (int x = 0; x < 4; x++) {
              o[x][4 * jj] *= a.x; o[x][4 * jj + 1] *= a.y; o[x][4 * jj + 2] *= a.x; o[x][4 * jj + 3] *= a.y;
            }
          }
        } else {
#pragma unroll
          for (int x = 0; x < 4; x++)
#pragma unroll
            for (int i = 0; i < 16; i++) o[x][i] = 0.f;
        }
        wg_fence();
#pragma unroll
        for (int kt = 0; kt < 4; kt++) {
          const uint64_t db = gdesc(sb + SM_P + tt * 4096) + kt * 2;
#pragma unroll
          for (int x = 0; x < 4; x++) wgmma_n32<1>(o[x], gdesc(sb + SM_K + tt * 32768 + x * 8192 + kt * 2048), db, 1);
        }
        wg_commit();
        wg_wait0();
        if (lane == 0) mbar_arrive(BAR(B_PVDONE + tt));
      }
      STAMP_T(12, 128);
      uint32_t* dst0 = S->opart + ((size_t)((2 * r + (w >> 1)) * 4 + ab) * 16 + as) * 64 + ((w & 1) * 8 + g) * 4;
#pragma unroll
      for (int jj = 0; jj < 4; jj++) {
#pragma unroll
        for (int e = 0; e < 2; e++) {
          const int head = 8 * jj + 2 * t + e;
          uint4 v;
          v.x = pack_bf16(o[0][4 * jj + e], o[0][4 * jj + 2 + e]);
          v.y = pack_bf16(o[1][4 * jj + e], o[1][4 * jj + 2 + e]);
          v.z = pack_bf16(o[2][4 * jj + e], o[2][4 * jj + 2 + e]);
          v.w = pack_bf16(o[3][4 * jj + e], o[3][4 * jj + 2 + e]);
          st_rlx16(dst0 + (size_t)head * (4 * 4 * 16 * 64), v);
        }
      }
      STAMP_T(13, 128);
    }

    {
      const int b = warp >> 1, sh = warp & 1, ch = lane & 15, sl = lane >> 4;
      const uint32_t* base = S->opart + ((size_t)((hd * 4 + qr) * 4 + b) * 16 + 8 * sh + sl) * 64 + ch * 4;
      const uint32_t* pp[4] = {base, base + 128, base + 256, base + 384};
      const uint32_t* sp = S->stats + ((hd * 4 + b) * 16 + (lane & 15)) * 2;
      uint2 st;
      {
        int it = 0;
        while (true) {
          st = ld_rlx8(sp);
          if ((st.x != SENT) & (st.y != SENT)) break;
          if (++it >= SPIN_LIMIT) { flag_err(5); break; }
        }
      }
      const float m = __uint_as_float(st.x), l = __uint_as_float(st.y);
      float M = m;
#pragma unroll
      for (int o_ = 1; o_ < 16; o_ <<= 1) M = fmaxf(M, __shfl_xor_sync(0xffffffffu, M, o_));
      const float e = ex2((m - M) * 1.4426950408889634f);
      float L = e * l;
#pragma unroll
      for (int o_ = 1; o_ < 16; o_ <<= 1) L += __shfl_xor_sync(0xffffffffu, L, o_);
      const float wgt = __fdiv_rn(e, L);
      uint4 v[4];
      poll16<4>(pp, v, 6);
      float acc[8];
#pragma unroll
      for (int i = 0; i < 8; i++) acc[i] = 0.f;
#pragma unroll
      for (int i = 0; i < 4; i++) {
        const float wi = __shfl_sync(0xffffffffu, wgt, 8 * sh + 2 * i + sl);
        float f[8];
        unpack8(v[i], f);
#pragma unroll
        for (int k = 0; k < 8; k++) acc[k] = fmaf(wi, f[k], acc[k]);
      }
      float rs[4];
#pragma unroll
      for (int k = 0; k < 4; k++) {
        const float keep = sl ? acc[k + 4] : acc[k], send = sl ? acc[k] : acc[k + 4];
        rs[k] = keep + __shfl_xor_sync(0xffffffffu, send, 16);
      }
      const uint32_t rowb = sb + SM_BA + warp * 272 + (64 * sl + 16 * (ch >> 3) + (ch & 7)) * 2;
#pragma unroll
      for (int k = 0; k < 4; k++) sts2(rowb + ((k >> 1) * 32 + (k & 1) * 8) * 2, (uint16_t)(pack_bf16(rs[k], 0.f) & 0xFFFFu));
    }
    STAMP_T(14, 0);
    mbar_wait(BAR(B_WUV));
    bar_sync(1, 256);
    STAMP_T(15, 0);
    {
      float o[4];
      gemv128<true, false>(o, sb + SM_K, sb + SM_BA, warp, lane);
      const float v0 = o[0] + o[1], v1 = o[2] + o[3];
      const float send = (g & 1) ? v0 : v1;
      const float recv = __shfl_xor_sync(0xffffffffu, send, 4);
      const uint32_t w = (g & 1) ? pack_bf16(recv, v1) : pack_bf16(v0, recv);
      const int d = 16 * warp + ((g & 1) ? g + 7 : g);
      st_rlx4(S->ctxp + ((hd * 4 + qr) * 4 + t) * 64 + d / 2, w);
    }
    {
      const int b = warp >> 1, cq = 2 * (warp & 1) + (lane >> 4), ch = lane & 15, sl = lane >> 4;
      const uint32_t* pp[1] = {S->ctxp + ((hd * 4 + cq) * 4 + b) * 64 + ch * 4};
      uint4 v[1];
      poll16<1>(pp, v, 7);
      float f[8], rs[4];
      unpack8(v[0], f);
#pragma unroll
      for (int k = 0; k < 4; k++) {
        const float keep = sl ? f[k + 4] : f[k], send = sl ? f[k] : f[k + 4];
        rs[k] = keep + __shfl_xor_sync(0xffffffffu, send, 16);
      }
      sts8(sb + SM_BB + warp * 272 + (8 * ch + 4 * sl) * 2, pack_bf16(rs[0], rs[1]), pack_bf16(rs[2], rs[3]));
    }
    STAMP_T(16, 0);
    mbar_wait(BAR(B_WO));
    bar_sync(1, 256);
    {
      float o[4];
      gemv128<true, false>(o, sb + SM_K + 32768, sb + SM_BB, warp, lane);
      const float v0 = o[0] + o[1], v1 = o[2] + o[3];
      const float send = (g & 1) ? v0 : v1;
      const float recv = __shfl_xor_sync(0xffffffffu, send, 4);
      const uint32_t w = (g & 1) ? pack_bf16(recv, v1) : pack_bf16(v0, recv);
      const int rho = t * 32 + 8 * qr + warp;
      st_rlx4(S->outp + (rho * 32 + hd) * 8 + ((g & 1) ? g + 7 : g) / 2, w);
    }
    STAMP_T(17, 0);
    if (j < 86) {
      if (warp < 4) {
        const uint32_t* mb = S->mod + warp * 1536 + lane * 8;
        const uint32_t* pm[4] = {mb + 768, mb + 772, mb + 1024, mb + 1028};
        uint4 mv[4];
        poll16<4>(pm, mv, 8);
        const uint32_t* px[2] = {S->x1 + warp * 256 + lane * 8, S->x1 + warp * 256 + lane * 8 + 4};
        uint4 xv[2];
        poll16<2>(px, xv, 9);
        float v[16], o[16], t8[8];
        unpack8(xv[0], t8);
#pragma unroll
        for (int i = 0; i < 8; i++) v[i] = t8[i];
        unpack8(xv[1], t8);
#pragma unroll
        for (int i = 0; i < 8; i++) v[8 + i] = t8[i];
        ln_row(v, o);
        uint32_t pk[8];
#pragma unroll
        for (int hf = 0; hf < 2; hf++) {
          float s8[8], c8[8];
          unpack8(mv[hf], s8);
          unpack8(mv[2 + hf], c8);
#pragma unroll
          for (int i = 0; i < 8; i += 2) {
            const float a = bfr(o[8 * hf + i] * bfr(1.f + c8[i])) + s8[i];
            const float b = bfr(o[8 * hf + i + 1] * bfr(1.f + c8[i + 1])) + s8[i + 1];
            pk[4 * hf + i / 2] = pack_bf16(a, b);
          }
        }
        const uint32_t a = sb + SM_BH2 + warp * 1040 + lane * 32;
        sts16(a, make_uint4(pk[0], pk[1], pk[2], pk[3]));
        sts16(a + 16, make_uint4(pk[4], pk[5], pk[6], pk[7]));
      }
      mbar_wait(BAR(B_W1));
      bar_sync(1, 256);
      STAMP_T(18, 0);
      {
        float o[4];
        gemv_narrow<2>(o, sb + SM_F2 + 16384 + warp * 64 * 32, sb + SM_BH2 + warp * 64 * 2, lane);
        const int row = g + 8 * (t >> 1), b0 = 2 * (t & 1);
        sts4f(sb + SM_RED + ((row * 4 + b0) * 8 + warp) * 4, (t >> 1) ? o[2] : o[0]);
        sts4f(sb + SM_RED + ((row * 4 + b0 + 1) * 8 + warp) * 4, (t >> 1) ? o[3] : o[1]);
      }
      bar_sync(1, 256);
      {
        float hv[4];
#pragma unroll
        for (int i = 0; i < 4; i++) {
          const int f = 2 * t + (i & 1) + 8 * (i >> 1);
          const uint32_t a = sb + SM_RED + (f * 4 + (g & 3)) * 32;
          const float4 u = lds16f(a), w = lds16f(a + 16);
          hv[i] = fmaxf(((u.x + u.y) + (u.z + u.w)) + ((w.x + w.y) + (w.z + w.w)), 0.f);
        }
        const uint32_t b0 = pack_bf16(hv[0], hv[1]), b1 = pack_bf16(hv[2], hv[3]);
        mbar_wait(BAR(B_W2));
        const int ro = (lane & 7) + 8 * (lane >> 4);
#pragma unroll
        for (int mt = 0; mt < 4; mt++) {
          uint32_t fa[4];
          ldsm4t(sb + SM_K + 65536 + warp * 2048 + ro * 128 + (((2 * mt + ((lane >> 3) & 1)) ^ (lane & 7)) << 4), fa);
          float o[4] = {0.f, 0.f, 0.f, 0.f};
          mma16816(o, fa, b0, b1);
          const float v0 = (t >> 1) ? o[2] : o[0], v1 = (t >> 1) ? o[3] : o[1];
          const float send = (g & 1) ? v0 : v1;
          const float recv = __shfl_xor_sync(0xffffffffu, send, 4);
          const uint32_t w = (g & 1) ? pack_bf16(recv, v1) : pack_bf16(v0, recv);
          const int b = 2 * (t & 1) + (g & 1), row = (g + 8 * (t >> 1)) & ~1;
          const int rho = b * 32 + 4 * warp + mt;
          st_rlx4(S->yp + ((size_t)rho * 88 + j) * 8 + row / 2, w);
        }
      }
      STAMP_T(19, 0);
    }
  }
}

}

typedef CUresult (*PFN_tmapEncodeTiled)(CUtensorMap*, CUtensorMapDataType, cuuint32_t, void*, const cuuint64_t*, const cuuint64_t*,
                                        const cuuint32_t*, const cuuint32_t*, CUtensorMapInterleave, CUtensorMapSwizzle,
                                        CUtensorMapL2promotion, CUtensorMapFloatOOBfill);

static void make_map(PFN_tmapEncodeTiled enc, CUtensorMap* m, const void* base, uint64_t cols, uint64_t rows, uint32_t boxc, uint32_t boxr) {
  cuuint64_t dims[2] = {cols, rows};
  cuuint64_t strides[1] = {cols * 2};
  cuuint32_t box[2] = {boxc, boxr};
  cuuint32_t es[2] = {1, 1};
  enc(m, CU_TENSOR_MAP_DATA_TYPE_BFLOAT16, 2, const_cast<void*>(base), dims, strides, box, es, CU_TENSOR_MAP_INTERLEAVE_NONE,
      CU_TENSOR_MAP_SWIZZLE_128B, CU_TENSOR_MAP_L2_PROMOTION_L2_128B, CU_TENSOR_MAP_FLOAT_OOB_FILL_NONE);
}

extern "C" void kernel_launch(void* const* d_in, const int* in_sizes, int n_in, void* d_out, int out_size) {
  (void)in_sizes; (void)n_in; (void)out_size;
  static PFN_tmapEncodeTiled enc = nullptr;
  if (!enc) {
    void* fn = nullptr;
    cudaDriverEntryPointQueryResult qr;
    cudaGetDriverEntryPoint("cuTensorMapEncodeTiled", &fn, cudaEnableDefault, &qr);
    enc = (PFN_tmapEncodeTiled)fn;
    cudaFuncSetAttribute(mla::decode_kernel, cudaFuncAttributeMaxDynamicSharedMemorySize, (int)mla::SMEM_BYTES);
  }
  mla::Params p;
  make_map(enc, &p.ckv, d_in[1], 512, 16384, 64, 64);
  make_map(enc, &p.wuk, d_in[3], 4096, 512, 64, 64);
  make_map(enc, &p.wuv, d_in[4], 4096, 512, 64, 32);
  make_map(enc, &p.wo, d_in[5], 512, 4096, 64, 64);
  make_map(enc, &p.w2, d_in[8], 512, 1376, 64, 16);
  p.x = (const __nv_bfloat16*)d_in[0];
  p.c = (const __nv_bfloat16*)d_in[9];
  p.wq = (const __nv_bfloat16*)d_in[2];
  p.wmod = (const __nv_bfloat16*)d_in[10];
  p.w1 = (const __nv_bfloat16*)d_in[7];
  p.out = (__nv_bfloat16*)d_out;
  mla::decode_kernel<<<mla::NCTA, mla::NTHR, mla::SMEM_BYTES, cudaStreamPerThread>>>(p);
}
```

```cpp
#include <cuda_runtime.h>
#include <cuda_bf16.h>
#include <cuda.h>
#include <stdint.h>

#define DEVINL __device__ __forceinline__

namespace mla {

constexpr int NCTA = 128;
constexpr int NTHR = 320;
constexpr int SPIN_LIMIT = 1 << 17;
constexpr int WINDOW = 4;
constexpr uint32_t S1_START = 4300, S2_START = 9400;
constexpr uint32_t D_Q = 350, D_O = 1600, D_CTX = 300, D_OUT = 300, D_X1 = 250, D_Y = 300;

struct __align__(1024) Scratch {
  uint32_t mod[4 * 3072];
  uint32_t qpart[32 * 2 * 8 * 64];
  uint32_t qabs[4 * 2 * 4096];
  uint32_t opart[32 * 4 * 4 * 16 * 64];
  uint32_t stats[2 * 32 * 4 * 16 * 2];
  uint32_t ctxp[32 * 4 * 4 * 64];
  uint32_t outp[128 * 32 * 8];
  uint32_t x1[4 * 256];
  uint32_t yp[128 * 88 * 8];
  uint32_t epoch[32];
};
constexpr uint32_t M_T16 = 0xFFFFu, M_F32 = 3u, M_PAR = 1u;

__device__ Scratch g_scr;

struct Scratch;
struct __align__(64) Params {
  const __nv_bfloat16 *x, *c, *wmod_ptr;
  __nv_bfloat16* out;
  Scratch* scr;
  uint64_t pad[3];
  CUtensorMap wq;
  CUtensorMap wuk;
  CUtensorMap ckv;
  CUtensorMap wmod;
  CUtensorMap wuv;
  CUtensorMap wo;
  CUtensorMap w1;
  CUtensorMap w2;
};

constexpr uint32_t SM_K = 0;
constexpr uint32_t SM_WUV = SM_K;
constexpr uint32_t SM_WO = SM_K + 32768;
constexpr uint32_t SM_WM2 = SM_K + 65536;
constexpr uint32_t SM_W2 = SM_K + 81920;
constexpr uint32_t SM_W1 = SM_K + 114688;
constexpr uint32_t SM_F1 = 131072;
constexpr uint32_t SM_XS = SM_F1;
constexpr uint32_t SM_F2 = 163840;
constexpr uint32_t SM_XL = SM_F2;
constexpr uint32_t SM_P = SM_F2 + 24576;
constexpr uint32_t SM_Q = 196608;
constexpr uint32_t SM_MISC = 212992;
constexpr uint32_t SM_BC = SM_MISC;
constexpr uint32_t SM_BH2 = SM_K + 98304;
constexpr uint32_t SM_BA = SM_BC + 4160;
constexpr uint32_t SM_BB = SM_BA + 2176;
constexpr uint32_t SM_RED = SM_BB + 2176;
constexpr uint32_t SM_LN = SM_RED + 2304;
constexpr uint32_t SM_ALPHA = SM_LN + 1024;
constexpr uint32_t SM_XMOD = SM_ALPHA + 512;
constexpr uint32_t SM_XQ = SM_XMOD + 256;
constexpr uint32_t SM_BAR = SM_XQ + 2048;
constexpr uint32_t SM_STAMP = SM_BAR + 512;
constexpr uint32_t SM_END = SM_STAMP;
constexpr uint32_t SMEM_BYTES = SM_END + 1024;
static_assert(SMEM_BYTES <= 232448, "smem");

enum {
  I_WQ = 0, I_WUK = 4, I_CKV = 8, I_WUV = 24, I_WO = 28, I_WMOD = 32, I_W2 = 34, I_W1 = 36, I_END = 38,
  B_XS = 38,
  B_XMOD = 42,
  B_PVDONE = 43,
  B_OUTP = 47,
  B_X1,
  B_YP,
  B_XQ,
  B_COUNT
};

DEVINL uint32_t smem_u32(const void* p) { return (uint32_t)__cvta_generic_to_shared(p); }
DEVINL void mbar_init(uint32_t bar, uint32_t cnt) { asm volatile("mbarrier.init.shared::cta.b64 [%0], %1;" ::"r"(bar), "r"(cnt) : "memory"); }
DEVINL void mbar_expect_tx(uint32_t bar, uint32_t bytes) { asm volatile("mbarrier.arrive.expect_tx.shared::cta.b64 _, [%0], %1;" ::"r"(bar), "r"(bytes) : "memory"); }
DEVINL void mbar_arrive(uint32_t bar) { asm volatile("mbarrier.arrive.shared::cta.b64 _, [%0];" ::"r"(bar) : "memory"); }
DEVINL void flag_err(int code) {
}
DEVINL void mbar_wait(uint32_t bar, uint32_t parity = 0) {
  asm volatile(
      "{\n.reg .pred p;\n.reg .u32 it;\nmov.u32 it, 0;\n"
      "WAIT_%=:\n"
      "mbarrier.try_wait.parity.shared::cta.b64 p, [%0], %1;\n"
      "@p bra DONE_%=;\n"
      "add.u32 it, it, 1;\n"
      "setp.lt.u32 p, it, %2;\n"
      "@p bra WAIT_%=;\n"
      "DONE_%=:\n}"
      ::"r"(bar), "r"(parity), "n"(SPIN_LIMIT) : "memory");
}
DEVINL void tma2d(uint32_t dst, const CUtensorMap* m, int c0, int c1, uint32_t bar, uint64_t pol) {
  asm volatile("cp.async.bulk.tensor.2d.shared::cluster.global.mbarrier::complete_tx::bytes.L2::cache_hint [%0], [%1, {%3, %4}], [%2], %5;"
               ::"r"(dst), "l"(m), "r"(bar), "r"(c0), "r"(c1), "l"(pol) : "memory");
}
template <int N>
DEVINL void mbar_wait_n(uint32_t bar) {
#pragma unroll
  for (int i = 0; i < N; i++) mbar_wait(bar + 8 * i);
}
DEVINL void cp16(uint32_t dst, const void* src) { asm volatile("cp.async.cg.shared.global.L2::128B [%0], [%1], 16;" ::"r"(dst), "l"(src) : "memory"); }
DEVINL void cp_commit() { asm volatile("cp.async.commit_group;" ::: "memory"); }
template <int N> DEVINL void cp_wait() { asm volatile("cp.async.wait_group %0;" ::"n"(N) : "memory"); }
DEVINL void bar_sync(int id, int n) { asm volatile("bar.sync %0, %1;" ::"r"(id), "r"(n) : "memory"); }
DEVINL void bar_arrive(int id, int n) { asm volatile("bar.arrive %0, %1;" ::"r"(id), "r"(n) : "memory"); }
DEVINL void fence_async_smem() { asm volatile("fence.proxy.async.shared::cta;" ::: "memory"); }

DEVINL uint4 ld_rlx16(const void* p) {
  uint4 v;
  asm volatile("ld.relaxed.gpu.global.v4.u32 {%0,%1,%2,%3}, [%4];" : "=r"(v.x), "=r"(v.y), "=r"(v.z), "=r"(v.w) : "l"(p) : "memory");
  return v;
}
DEVINL uint2 ld_rlx8(const void* p) {
  uint2 v;
  asm volatile("ld.relaxed.gpu.global.v2.u32 {%0,%1}, [%2];" : "=r"(v.x), "=r"(v.y) : "l"(p) : "memory");
  return v;
}
DEVINL uint32_t ld_rlx4(const void* p) {
  uint32_t v;
  asm volatile("ld.relaxed.gpu.global.u32 %0, [%1];" : "=r"(v) : "l"(p) : "memory");
  return v;
}
DEVINL void st_rlx16(void* p, uint4 v) {
  asm volatile("st.relaxed.gpu.global.v4.u32 [%0], {%1,%2,%3,%4};" ::"l"(p), "r"(v.x), "r"(v.y), "r"(v.z), "r"(v.w) : "memory");
}
DEVINL void st_rlx128(void* p, uint32_t x, uint32_t y, uint32_t z, uint32_t w) {
  asm volatile("{\n.reg .b128 q;\n.reg .b64 lo, hi;\nmov.b64 lo, {%1, %2};\nmov.b64 hi, {%3, %4};\nmov.b128 q, {lo, hi};\n"
               "st.relaxed.gpu.global.b128 [%0], q;\n}" ::"l"(p), "r"(x), "r"(y), "r"(z), "r"(w) : "memory");
}
DEVINL void ld_rlx128_if(uint4& v, const void* p, uint32_t go) {
  asm volatile("{\n.reg .pred p;\n.reg .b128 q;\n.reg .b64 lo, hi;\nsetp.ne.u32 p, %5, 0;\n"
               "mov.b64 lo, {%0, %1};\nmov.b64 hi, {%2, %3};\nmov.b128 q, {lo, hi};\n"
               "@p ld.relaxed.gpu.global.b128 q, [%4];\n"
               "mov.b128 {lo, hi}, q;\nmov.b64 {%0, %1}, lo;\nmov.b64 {%2, %3}, hi;\n}"
               : "+r"(v.x), "+r"(v.y), "+r"(v.z), "+r"(v.w) : "l"(p), "r"(go) : "memory");
}
DEVINL void st_rlx8(void* p, uint2 v) { asm volatile("st.relaxed.gpu.global.v2.u32 [%0], {%1,%2};" ::"l"(p), "r"(v.x), "r"(v.y) : "memory"); }
DEVINL void st_rlx4(void* p, uint32_t v) { asm volatile("st.relaxed.gpu.global.u32 [%0], %1;" ::"l"(p), "r"(v) : "memory"); }
DEVINL uint4 ldg16(const void* p) {
  uint4 v;
  asm volatile("ld.global.nc.v4.u32 {%0,%1,%2,%3}, [%4];" : "=r"(v.x), "=r"(v.y), "=r"(v.z), "=r"(v.w) : "l"(p));
  return v;
}
DEVINL uint32_t tag_acc(uint32_t bad, const uint4& v, uint32_t t) {
  uint32_t u, w, r;
  asm("lop3.b32 %0, %1, %2, %3, 0x7E;" : "=r"(u) : "r"(v.x), "r"(v.y), "r"(t));
  asm("lop3.b32 %0, %1, %2, %3, 0x7E;" : "=r"(w) : "r"(v.z), "r"(v.w), "r"(t));
  asm("lop3.b32 %0, %1, %2, %3, 0xFE;" : "=r"(r) : "r"(u), "r"(w), "r"(bad));
  return r;
}
DEVINL void ld_rlx16_if(uint4& v, const void* p, uint32_t go) {
  asm volatile("{\n.reg .pred p;\nsetp.ne.u32 p, %5, 0;\n@p ld.relaxed.gpu.global.v4.u32 {%0,%1,%2,%3}, [%4];\n}"
               : "+r"(v.x), "+r"(v.y), "+r"(v.z), "+r"(v.w) : "l"(p), "r"(go) : "memory");
}
template <int N, bool FIRST = true>
DEVINL void poll16(const uint32_t* const (&p)[N], uint4 (&v)[N], uint32_t tag, uint32_t mask, int code) {
  if (FIRST) {
#pragma unroll
    for (int i = 0; i < N; i++) v[i] = ld_rlx16(p[i]);
  }
  int it = 0;
#pragma unroll 1
  while (true) {
    uint32_t bad[N], any = 0;
#pragma unroll
    for (int i = 0; i < N; i++) { bad[i] = tag_acc(0, v[i], tag) & mask; any |= bad[i]; }
    if (!__any_sync(0xffffffffu, any != 0)) break;
    if (++it >= SPIN_LIMIT) { flag_err(code); break; }
#pragma unroll
    for (int i = 0; i < N; i++) ld_rlx16_if(v[i], p[i], bad[i]);
  }
}
DEVINL uint32_t poll4(const uint32_t* p, uint32_t tag, uint32_t mask, int code) {
  uint32_t v;
  int it = 0;
#pragma unroll 1
  while (__any_sync(0xffffffffu, (((v = ld_rlx4(p)) ^ tag) & mask) != 0)) {
    if (++it >= SPIN_LIMIT) { flag_err(code); break; }
  }
  return v;
}
DEVINL void gate4(const uint32_t* p, bool act, uint32_t tag, uint32_t mask, int code) {
  int it = 0;
#pragma unroll 1
  while (true) {
    const uint32_t v = act ? ld_rlx4(p) : tag;
    if (__all_sync(0xffffffffu, ((v ^ tag) & mask) == 0)) break;
    if (++it >= SPIN_LIMIT) { flag_err(code); break; }
  }
}
DEVINL void pause(uint32_t clks) {
  const uint32_t t0 = (uint32_t)clock();
  while ((uint32_t)clock() - t0 < clks) { }
}
DEVINL uint32_t hi2(uint32_t a, uint32_t b) { return __byte_perm(a, b, 0x7632); }

DEVINL void sts16(uint32_t a, uint4 v) { asm volatile("st.shared.v4.b32 [%0], {%1,%2,%3,%4};" ::"r"(a), "r"(v.x), "r"(v.y), "r"(v.z), "r"(v.w) : "memory"); }
DEVINL void sts8(uint32_t a, uint32_t x, uint32_t y) { asm volatile("st.shared.v2.b32 [%0], {%1,%2};" ::"r"(a), "r"(x), "r"(y) : "memory"); }
DEVINL void sts4(uint32_t a, uint32_t x) { asm volatile("st.shared.b32 [%0], %1;" ::"r"(a), "r"(x) : "memory"); }
DEVINL void sts4f(uint32_t a, float x) { asm volatile("st.shared.f32 [%0], %1;" ::"r"(a), "f"(x) : "memory"); }
DEVINL void sts2(uint32_t a, uint16_t x) { asm volatile("st.shared.b16 [%0], %1;" ::"r"(a), "h"(x) : "memory"); }
DEVINL uint4 lds16(uint32_t a) {
  uint4 v;
  asm volatile("ld.shared.v4.b32 {%0,%1,%2,%3}, [%4];" : "=r"(v.x), "=r"(v.y), "=r"(v.z), "=r"(v.w) : "r"(a) : "memory");
  return v;
}
DEVINL float4 lds16f(uint32_t a) {
  float4 v;
  asm volatile("ld.shared.v4.f32 {%0,%1,%2,%3}, [%4];" : "=f"(v.x), "=f"(v.y), "=f"(v.z), "=f"(v.w) : "r"(a) : "memory");
  return v;
}
DEVINL float2 lds8f(uint32_t a) {
  float2 v;
  asm volatile("ld.shared.v2.f32 {%0,%1}, [%2];" : "=f"(v.x), "=f"(v.y) : "r"(a) : "memory");
  return v;
}
DEVINL float lds4f(uint32_t a) {
  float v;
  asm volatile("ld.shared.f32 %0, [%1];" : "=f"(v) : "r"(a) : "memory");
  return v;
}

DEVINL uint32_t pack_bf16(float lo, float hi) {
  uint32_t r;
  asm("cvt.rn.bf16x2.f32 %0, %1, %2;" : "=r"(r) : "f"(hi), "f"(lo));
  return r;
}
DEVINL float bf_lo(uint32_t w) { return __uint_as_float(w << 16); }
DEVINL float bf_hi(uint32_t w) { return __uint_as_float(w & 0xFFFF0000u); }
DEVINL float bfr(float x) { return __uint_as_float(pack_bf16(x, 0.f) << 16); }
DEVINL float ex2(float x) {
  float y;
  asm("ex2.approx.ftz.f32 %0, %1;" : "=f"(y) : "f"(x));
  return y;
}
DEVINL void unpack8(const uint4& v, float (&f)[8]) {
  f[0] = bf_lo(v.x); f[1] = bf_hi(v.x); f[2] = bf_lo(v.y); f[3] = bf_hi(v.y);
  f[4] = bf_lo(v.z); f[5] = bf_hi(v.z); f[6] = bf_lo(v.w); f[7] = bf_hi(v.w);
}

DEVINL void ldsm4(uint32_t a, uint32_t (&r)[4]) {
  asm volatile("ldmatrix.sync.aligned.m8n8.x4.shared.b16 {%0,%1,%2,%3}, [%4];" : "=r"(r[0]), "=r"(r[1]), "=r"(r[2]), "=r"(r[3]) : "r"(a) : "memory");
}
DEVINL void ldsm4t(uint32_t a, uint32_t (&r)[4]) {
  asm volatile("ldmatrix.sync.aligned.m8n8.x4.trans.shared.b16 {%0,%1,%2,%3}, [%4];" : "=r"(r[0]), "=r"(r[1]), "=r"(r[2]), "=r"(r[3]) : "r"(a) : "memory");
}
DEVINL void stsm4t(uint32_t a, uint32_t r0, uint32_t r1, uint32_t r2, uint32_t r3) {
  asm volatile("stmatrix.sync.aligned.m8n8.x4.trans.shared.b16 [%0], {%1,%2,%3,%4};" ::"r"(a), "r"(r0), "r"(r1), "r"(r2), "r"(r3) : "memory");
}
DEVINL void mma16816(float (&d)[4], const uint32_t (&a)[4], uint32_t b0, uint32_t b1) {
  asm volatile("mma.sync.aligned.m16n8k16.row.col.f32.bf16.bf16.f32 {%0,%1,%2,%3}, {%4,%5,%6,%7}, {%8,%9}, {%0,%1,%2,%3};"
               : "+f"(d[0]), "+f"(d[1]), "+f"(d[2]), "+f"(d[3])
               : "r"(a[0]), "r"(a[1]), "r"(a[2]), "r"(a[3]), "r"(b0), "r"(b1));
}
DEVINL uint64_t gdesc(uint32_t addr) {
  return (uint64_t)((addr & 0x3FFFF) >> 4) | (1ull << 16) | (64ull << 32) | (1ull << 62);
}
template <int TA>
DEVINL void wgmma_n32(float (&d)[16], uint64_t da, uint64_t db, int scale_d) {
  asm volatile(
      "{\n.reg .pred p;\nsetp.ne.b32 p, %18, 0;\n"
      "wgmma.mma_async.sync.aligned.m64n32k16.f32.bf16.bf16 "
      "{%0,%1,%2,%3,%4,%5,%6,%7,%8,%9,%10,%11,%12,%13,%14,%15}, %16, %17, p, 1, 1, %19, 0;\n}\n"
      : "+f"(d[0]), "+f"(d[1]), "+f"(d[2]), "+f"(d[3]), "+f"(d[4]), "+f"(d[5]), "+f"(d[6]), "+f"(d[7]),
        "+f"(d[8]), "+f"(d[9]), "+f"(d[10]), "+f"(d[11]), "+f"(d[12]), "+f"(d[13]), "+f"(d[14]), "+f"(d[15])
      : "l"(da), "l"(db), "r"(scale_d), "n"(TA));
}
DEVINL void wg_fence() { asm volatile("wgmma.fence.sync.aligned;" ::: "memory"); }
DEVINL void wg_commit() { asm volatile("wgmma.commit_group.sync.aligned;" ::: "memory"); }
DEVINL void wg_wait0() { asm volatile("wgmma.wait_group.sync.aligned 0;" ::: "memory"); }

template <bool TRANS, bool DUP>
DEVINL void gemv128(float (&o)[4], uint32_t tile, uint32_t bs, int warp, int lane) {
  float a0[4] = {0.f, 0.f, 0.f, 0.f}, a1[4] = {0.f, 0.f, 0.f, 0.f};
  const uint32_t brow = bs + (DUP ? (lane & 3) : (lane & 7)) * 272 + (lane >> 3) * 16;
  uint32_t abase;
  if (TRANS) {
    const int ro = (lane & 7) + 8 * (lane >> 4);
    const int ch = 2 * (warp & 3) + ((lane >> 3) & 1);
    abase = tile + (warp >> 2) * 16384 + ro * 128 + ((ch ^ (lane & 7)) << 4);
  } else {
    abase = tile + (16 * warp + (lane & 7) + 8 * ((lane >> 3) & 1)) * 128;
  }
#pragma unroll
  for (int kp = 0; kp < 4; kp++) {
    uint32_t b[4], fa[4], fb[4];
    ldsm4(brow + kp * 64, b);
    if (TRANS) {
      ldsm4t(abase + (2 * kp) * 2048, fa);
      ldsm4t(abase + (2 * kp + 1) * 2048, fb);
    } else {
      const int k0 = 2 * kp, k1 = 2 * kp + 1;
      ldsm4(abase + (k0 >> 2) * 16384 + (((2 * (k0 & 3) + (lane >> 4)) ^ (lane & 7)) << 4), fa);
      ldsm4(abase + (k1 >> 2) * 16384 + (((2 * (k1 & 3) + (lane >> 4)) ^ (lane & 7)) << 4), fb);
    }
    mma16816(a0, fa, b[0], b[1]);
    mma16816(a1, fb, b[2], b[3]);
  }
#pragma unroll
  for (int i = 0; i < 4; i++) o[i] = a0[i] + a1[i];
}

template <int NKP>
DEVINL void gemv_narrow(float (&o)[4], uint32_t tile  , uint32_t bs  , int lane) {
  float a0[4] = {0.f, 0.f, 0.f, 0.f}, a1[4] = {0.f, 0.f, 0.f, 0.f};
  const uint32_t brow = bs + (lane & 3) * 1040 + (lane >> 3) * 16;
  const int ro = (lane & 7) + 8 * (lane >> 4);
  const uint32_t abase = tile + ro * 32 + (((((lane >> 3) & 1)) ^ ((ro >> 2) & 1)) << 4);
#pragma unroll 2
  for (int kp = 0; kp < NKP; kp++) {
    uint32_t b[4], fa[4], fb[4];
    ldsm4(brow + kp * 64, b);
    ldsm4t(abase + (2 * kp) * 512, fa);
    ldsm4t(abase + (2 * kp + 1) * 512, fb);
    mma16816(a0, fa, b[0], b[1]);
    mma16816(a1, fb, b[2], b[3]);
  }
#pragma unroll
  for (int i = 0; i < 4; i++) o[i] = a0[i] + a1[i];
}

DEVINL float colsum16(float (&v)[16], int lane) {
  const bool h4 = lane & 16, h3 = lane & 8, h2 = lane & 4, h1 = lane & 2;
  float a[8], b[4], c[2];
#pragma unroll
  for (int i = 0; i < 8; i++) {
    float keep = h4 ? v[i + 8] : v[i], send = h4 ? v[i] : v[i + 8];
    a[i] = keep + __shfl_xor_sync(0xffffffffu, send, 16);
  }
#pragma unroll
  for (int i = 0; i < 4; i++) {
    float keep = h3 ? a[i + 4] : a[i], send = h3 ? a[i] : a[i + 4];
    b[i] = keep + __shfl_xor_sync(0xffffffffu, send, 8);
  }
#pragma unroll
  for (int i = 0; i < 2; i++) {
    float keep = h2 ? b[i + 2] : b[i], send = h2 ? b[i] : b[i + 2];
    c[i] = keep + __shfl_xor_sync(0xffffffffu, send, 4);
  }
  float keep = h1 ? c[1] : c[0], send = h1 ? c[0] : c[1];
  float d = keep + __shfl_xor_sync(0xffffffffu, send, 2);
  return d + __shfl_xor_sync(0xffffffffu, d, 1);
}

DEVINL uint32_t bf2_add(uint32_t a, uint32_t b) { uint32_t r; asm("add.rn.bf16x2 %0, %1, %2;" : "=r"(r) : "r"(a), "r"(b)); return r; }
DEVINL uint32_t bf2_sub(uint32_t a, uint32_t b) { uint32_t r; asm("sub.rn.bf16x2 %0, %1, %2;" : "=r"(r) : "r"(a), "r"(b)); return r; }
DEVINL uint32_t bf2_max(uint32_t a, uint32_t b) { uint32_t r; asm("max.bf16x2 %0, %1, %2;" : "=r"(r) : "r"(a), "r"(b)); return r; }
DEVINL uint32_t bf2_mul(uint32_t a, uint32_t b) { uint32_t r; asm("mul.rn.bf16x2 %0, %1, %2;" : "=r"(r) : "r"(a), "r"(b)); return r; }

DEVINL void ln_row(uint32_t (&w)[8]) {
  float v[16], s = 0.f;
#pragma unroll
  for (int i = 0; i < 8; i++) { v[2 * i] = bf_lo(w[i]); v[2 * i + 1] = bf_hi(w[i]); s += v[2 * i] + v[2 * i + 1]; }
  float mean = s * (1.f / 16.f), m2 = 0.f;
#pragma unroll
  for (int i = 0; i < 16; i++) { const float d = v[i] - mean; m2 = fmaf(d, d, m2); }
  float hn = 8.f;
#pragma unroll 1
  for (int o_ = 1; o_ < 32; o_ <<= 1) {
    const float mo = __shfl_xor_sync(0xffffffffu, mean, o_);
    const float so = __shfl_xor_sync(0xffffffffu, m2, o_);
    const float d = mo - mean;
    m2 = fmaf(d * d, hn, m2 + so);
    mean = 0.5f * (mean + mo);
    hn *= 2.f;
  }
  const uint32_t mb = pack_bf16(mean, mean);
  float sq, rinv;
  asm("sqrt.approx.f32 %0, %1;" : "=f"(sq) : "f"(bfr(bfr(m2 * (1.f / 512.f)) + 1e-5f)));
  asm("rcp.approx.f32 %0, %1;" : "=f"(rinv) : "f"(bfr(sq)));
#pragma unroll
  for (int i = 0; i < 8; i++) {
    const uint32_t xc = bf2_sub(w[i], mb);
    w[i] = pack_bf16(bf_lo(xc) * rinv, bf_hi(xc) * rinv);
  }
}
DEVINL uint32_t modulate(uint32_t ln, uint32_t scale, uint32_t shift) {
  return bf2_add(bf2_mul(ln, bf2_add(scale, 0x3F803F80u)), shift);
}

#define STAMP(i)
#define STAMP_T(i, t) STAMP(i)

__global__ void __cluster_dims__(2, 1, 1) __launch_bounds__(NTHR, 1)
decode_kernel(const __grid_constant__ Params P) {
  extern __shared__ uint8_t smem_raw[];
  uint32_t sb = (smem_u32(smem_raw) + 1023u) & ~1023u;
  asm volatile("mov.u32 %0, %0;" : "+r"(sb));
  const int tid = threadIdx.x, lane = tid & 31;
  const int warp = __shfl_sync(0xffffffffu, tid >> 5, 0);
  const int j = blockIdx.x;
  const int r = j & 1;
  const int hd = j >> 2, qr = j & 3;
  const int ab = j >> 5, as = (j & 31) >> 1;
  Scratch* const S = P.scr;
  const uint32_t clk0 = (uint32_t)clock();
  const uint32_t bar0 = sb + SM_BAR;
#define BAR(i) (bar0 + 8u * (i))

  uint4 c_raw, x_raw0, x_raw1;
  uint32_t ep = 0;
  if (warp == 8 && lane == 0) {
#pragma unroll
    for (int i = 0; i < 25; i++) mbar_init(BAR(i), 1);
    asm volatile("fence.mbarrier_init.release.cluster;" ::: "memory");
  } else if (warp == 9 && lane == 0) {
#pragma unroll
    for (int i = 25; i < B_COUNT; i++)
      mbar_init(BAR(i), (i == B_OUTP || i == B_YP) ? 8 : (i >= B_PVDONE && i < B_PVDONE + 4) ? 4 : (i >= B_XS && i < B_XS + 4) ? 2 : 1);
#pragma unroll
    for (int i = 0; i < 4; i++) mbar_expect_tx(BAR(B_XS + i), 8192);
    mbar_expect_tx(BAR(B_XMOD), 256);
    mbar_expect_tx(BAR(B_XQ), 2048);
    asm volatile("fence.mbarrier_init.release.cluster;" ::: "memory");
  }
  __syncwarp();
  if (warp < 8) {
    c_raw = ldg16(P.c + tid * 8);
    const int row = tid >> 1, ch = tid & 1;
    const uint32_t dst = sb + SM_Q + row * 32 + ((ch ^ ((row >> 2) & 1)) << 4);
    const __nv_bfloat16* src = P.wmod_ptr + (size_t)(256 * r + row) * 3072 + 16 * (j >> 1) + 8 * ch;
    cp16(dst, src);
    cp16(dst + 128 * 32, src + (size_t)128 * 3072);
    cp_commit();
    if (warp < 4) {
      x_raw0 = ldg16(P.x + warp * 512 + lane * 16);
      x_raw1 = ldg16(P.x + warp * 512 + lane * 16 + 8);
    }
  }
  if (warp != 8) ep = ld_rlx4(S->epoch);
  asm volatile("barrier.cluster.arrive.relaxed.aligned;" ::: "memory");
  __syncthreads();
  STAMP_T(27, 0);

  if (warp == 8) {
    if (lane == 0) {
      uint64_t pol;
      asm volatile("createpolicy.fractional.L2::evict_first.b64 %0, 1.0;" : "=l"(pol));
      {
        const CUtensorMap* maps = &P.wq;
#pragma unroll
        for (int k = 0; k < 8; k++) asm volatile("prefetch.tensormap [%0];" ::"l"(maps + k) : "memory");
      }
      const int n_items = j < 86 ? (int)I_END : (int)I_W2;
#pragma unroll 1
      for (int i = 0; i < n_items; i++) {
        if (i >= WINDOW) mbar_wait(BAR(i - WINDOW));
        const CUtensorMap* m;
        int c0, c1, nsub = 1, dc0 = 0, dc1 = 0;
        uint32_t dst, dstep = 0;
        if (i < I_CKV) {
          const int s = i & 3;
          m = i < I_WUK ? &P.wq : &P.wuk;
          c0 = hd * 128 + (s & 1) * 64; c1 = qr * 128 + (s >> 1) * 64;
          dst = (i < I_WUK ? SM_F1 : SM_F2) + (s & 1) * 16384 + (s >> 1) * 8192;
        } else if (i < I_WUV) {
          const int s = i - I_CKV;
          m = &P.ckv;
          c0 = r * 256 + (s & 3) * 64; c1 = ab * 4096 + as * 256 + (s >> 2) * 64;
          dst = SM_K + s * 8192;
        } else if (i < I_WO) {
          const int s = i - I_WUV;
          if (s == 0) mbar_wait(BAR(B_PVDONE + 0));
          m = &P.wuv;
          c0 = hd * 128 + (s >> 1) * 64; c1 = 256 * (qr >> 1) + 128 * (s & 1) + 32 * (qr & 1);
          dst = SM_WUV + s * 8192;
          nsub = 2; dc1 = 64; dstep = 4096;
        } else if (i < I_WMOD) {
          const int s = i - I_WO;
          if (s == 0) mbar_wait(BAR(B_PVDONE + 1));
          m = &P.wo;
          c0 = qr * 128 + (s & 1) * 64; c1 = hd * 128 + (s >> 1) * 64;
          dst = SM_WO + (s & 1) * 16384 + (s >> 1) * 8192;
        } else if (i < I_W2) {
          const int s = i - I_WMOD;
          if (s == 0) mbar_wait(BAR(B_PVDONE + 2));
          m = &P.wmod;
          c0 = 1024 + 16 * j; c1 = 256 * s;
          dst = SM_WM2 + s * 8192;
        } else if (i < I_W1) {
          const int s = i - I_W2;
          m = &P.w2;
          c0 = 256 * s; c1 = 16 * j;
          dst = SM_W2 + s * 8192;
          nsub = 4; dc0 = 64; dstep = 2048;
        } else {
          const int s = i - I_W1;
          if (s == 0) mbar_wait(BAR(B_PVDONE + 3));
          m = &P.w1;
          c0 = 16 * j; c1 = 256 * s;
          dst = SM_W1 + s * 8192;
        }
        mbar_expect_tx(BAR(i), 8192);
#pragma unroll 1
        for (int u = 0; u < nsub; u++) tma2d(sb + dst + u * dstep, m, c0 + u * dc0, c1 + u * dc1, BAR(i), pol);
      }
    }
  } else if (warp == 9) {
    asm volatile("add.u32 %0, %0, 1;" : "+r"(ep));
    const uint32_t par = ep & 1;
    const int mg = j & 31;
    const int mcol = 16 * mg + ((lane >> 4) & 1) * 8 + ((lane >> 3) & 1) * 4 + ((lane >> 2) & 1) * 2 + ((lane >> 1) & 1);
    uint32_t* const x1p = S->x1 + ab * 256 + mcol / 2;
    uint32_t* const m2p = S->mod + 2 * (lane & 1) * 3072 + 1024 + 16 * j + (lane >> 2) + 8 * ((lane >> 1) & 1);
    st_rlx4(m2p, ep ^ 1);
    st_rlx4(m2p + 3072, ep ^ 1);
    if ((lane & 3) == 0) st_rlx4(x1p, par ^ 1);
    const float xv = __bfloat162float(P.x[ab * 512 + mcol]);
    mbar_wait_n<2>(BAR(I_WMOD));
    {
      float o[4];
      gemv_narrow<16>(o, sb + SM_WM2, sb + SM_BC, lane);
      const uint32_t tg = ep & M_T16;
      st_rlx4(m2p, (pack_bf16(0.f, (lane & 2) ? o[2] : o[0]) & 0xFFFF0000u) | tg);
      st_rlx4(m2p + 3072, (pack_bf16(0.f, (lane & 2) ? o[3] : o[1]) & 0xFFFF0000u) | tg);
    }
    STAMP(24);
    const uint32_t* gp = S->mod + ab * 3072 + 1024 + mcol;
    const float ga = bf_hi(poll4(gp, ep, M_T16, 20));
    const float gb = bf_hi(poll4(gp + 1536, ep, M_T16, 21));
    float x1v = 0.f;
#pragma unroll 1
    for (int pass = 0; pass < 2; pass++) {
      if (pass == 0 || j < 86) { mbar_wait(BAR(pass == 0 ? B_OUTP : B_YP)); pause(pass == 0 ? D_OUT : D_Y); }
      else gate4(S->yp + j * 88 * 8, lane == 0, par, M_PAR, 24);
      const uint32_t* p0 = (pass == 0 ? S->outp + j * 32 * 8 : S->yp + j * 88 * 8) + lane * 8;
      const bool a1 = pass == 1, a2 = pass == 1 && lane + 64 < 86;
      uint4 v[6];
      {
        const uint4 z = make_uint4(par, par, par, par);
        v[2] = z; v[3] = z; v[4] = z; v[5] = z;
        v[0] = ld_rlx16(p0); v[1] = ld_rlx16(p0 + 4);
        ld_rlx16_if(v[2], p0 + 256, a1); ld_rlx16_if(v[3], p0 + 260, a1);
        ld_rlx16_if(v[4], p0 + 512, a2); ld_rlx16_if(v[5], p0 + 516, a2);
        const uint32_t* pp[6] = {p0, p0 + 4, p0 + 256, p0 + 260, p0 + 512, p0 + 516};
        poll16<6, false>(pp, v, par, M_PAR, 22);
      }
      __syncwarp();
      STAMP(20 + pass);
      float f[16];
#pragma unroll
      for (int hf = 0; hf < 2; hf++) {
        const uint32_t w0[4] = {v[hf].x, v[hf].y, v[hf].z, v[hf].w};
        const uint32_t w1[4] = {v[2 + hf].x, v[2 + hf].y, v[2 + hf].z, v[2 + hf].w};
        const uint32_t w2[4] = {v[4 + hf].x, v[4 + hf].y, v[4 + hf].z, v[4 + hf].w};
#pragma unroll
        for (int i = 0; i < 4; i++) {
          f[8 * hf + 2 * i] = (bf_lo(w0[i] ^ par) + bf_lo(w1[i] ^ par)) + bf_lo(w2[i] ^ par);
          f[8 * hf + 2 * i + 1] = (bf_hi(w0[i]) + bf_hi(w1[i])) + bf_hi(w2[i]);
        }
      }
      const float sum = bfr(colsum16(f, lane));
      if (pass == 0) {
        x1v = bfr(xv + bfr(ga * sum));
        const float nb = __shfl_xor_sync(0xffffffffu, x1v, 2);
        if ((lane & 3) == 0) st_rlx4(x1p, (pack_bf16(x1v, nb) & ~1u) | par);
        if (lane == 0) mbar_arrive(BAR(B_X1));
        __syncwarp();
        STAMP(25);
      } else {
        const float o = bfr(x1v + bfr(gb * sum));
        const float nb = __shfl_xor_sync(0xffffffffu, o, 2);
        if ((lane & 3) == 0) reinterpret_cast<uint32_t*>(P.out)[ab * 256 + mcol / 2] = pack_bf16(o, nb);
      }
    }
    if (j == 0 && lane == 0) st_rlx4(S->epoch, ep);
    STAMP(26);
  } else {
    const int g = lane >> 2, t = lane & 3;
    {
      float f[8];
      unpack8(c_raw, f);
#pragma unroll
      for (int i = 0; i < 8; i++) f[i] = __fdividef(f[i], 1.f + __expf(-f[i]));
      uint4 w = make_uint4(pack_bf16(f[0], f[1]), pack_bf16(f[2], f[3]), pack_bf16(f[4], f[5]), pack_bf16(f[6], f[7]));
      sts16(sb + SM_BC + (tid >> 6) * 1040 + (tid & 63) * 16, w);
    }
    asm volatile("add.u32 %0, %0, 1;" : "+r"(ep));
    const uint32_t par = ep & 1, tg2 = ep & M_F32;
    uint32_t* const modp = S->mod + (tid >> 4) * 3072 + 16 * (j >> 1) + (tid & 15);
    uint32_t* const qpp = S->qpart + ((j >> 1) * 8 + warp) * 64 + r * 32 + lane;
    uint32_t* qap;
    {
      const int b = 2 * (t & 1) + (g & 1);
      const int cl = 128 * (qr & 1) + 16 * warp + 8 * (t >> 1);
      qap = S->qabs + (b * 2 + (qr >> 1)) * 4096 + (cl >> 6) * 1024 + hd * 32 + ((((cl & 63) >> 3) ^ (hd & 7)) << 2);
    }
    if (warp < 2 && r == 0) st_rlx4(modp, ep ^ 1);
    st_rlx4(qpp, ep ^ 1);
    if (lane < 8) st_rlx128(qap, par ^ 1, 0, 0, 0);
    cp_wait<0>();
    asm volatile("barrier.cluster.wait.acquire.aligned;" ::: "memory");
    bar_sync(1, 256);
    STAMP_T(0, 0);
    {
      float o[4];
      gemv_narrow<1>(o, sb + SM_Q + warp * 32 * 32, sb + SM_BC + (256 * r + 32 * warp) * 2, lane);
      const int row = g + 8 * (t >> 1), b0 = 2 * (t & 1);
      sts4f(sb + SM_RED + warp * 256 + (b0 * 16 + row) * 4, (t >> 1) ? o[2] : o[0]);
      sts4f(sb + SM_RED + warp * 256 + ((b0 + 1) * 16 + row) * 4, (t >> 1) ? o[3] : o[1]);
    }
    bar_sync(1, 256);
    if (warp < 2) {
      float s = 0.f;
#pragma unroll
      for (int w = 0; w < 8; w++) s += lds4f(sb + SM_RED + w * 256 + tid * 4);
      if (r == 1) {
        uint32_t ra, rb;
        asm volatile("mapa.shared::cluster.u32 %0, %1, %2;" : "=r"(ra) : "r"(sb + SM_XMOD + tid * 4), "r"(0));
        asm volatile("mapa.shared::cluster.u32 %0, %1, %2;" : "=r"(rb) : "r"(BAR(B_XMOD)), "r"(0));
        asm volatile("st.async.weak.shared::cluster.mbarrier::complete_tx::bytes.b32 [%0], %1, [%2];" ::"r"(ra), "r"(__float_as_uint(s)), "r"(rb) : "memory");
      } else {
        mbar_wait(BAR(B_XMOD));
        s += lds4f(sb + SM_XMOD + tid * 4);
        st_rlx4(modp, (pack_bf16(0.f, s) & 0xFFFF0000u) | (ep & M_T16));
      }
    }
    STAMP_T(1, 0);
    if (warp < 4) {
      uint32_t xw[8] = {x_raw0.x, x_raw0.y, x_raw0.z, x_raw0.w, x_raw1.x, x_raw1.y, x_raw1.z, x_raw1.w};
      ln_row(xw);
      if ((lane >> 3) == qr) {
        const uint32_t a = sb + SM_LN + warp * 256 + (lane & 7) * 32;
        sts16(a, make_uint4(xw[0], xw[1], xw[2], xw[3]));
        sts16(a + 16, make_uint4(xw[4], xw[5], xw[6], xw[7]));
      }
      __syncwarp();
    }
    STAMP(29);
    if (warp < 4) {
      const int b = warp, c4 = lane;
      while ((uint32_t)clock() - clk0 < S1_START) { }
      const uint32_t* sp_ = S->mod + b * 3072 + 128 * qr + 4 * c4;
      const uint32_t* pp[2] = {sp_, sp_ + 512};
      uint4 v[2];
      poll16<2>(pp, v, ep, M_T16, 2);
      const float2 ln = lds8f(sb + SM_LN + b * 256 + c4 * 8);
      sts8(sb + SM_BA + b * 272 + c4 * 8,
           modulate(__float_as_uint(ln.x), hi2(v[1].x, v[1].y), hi2(v[0].x, v[0].y)),
           modulate(__float_as_uint(ln.y), hi2(v[1].z, v[1].w), hi2(v[0].z, v[0].w)));
    }
    STAMP_T(2, 0);
    if (warp == 7) mbar_wait_n<4>(BAR(I_WQ));
    bar_sync(1, 256);
    STAMP_T(3, 0);
    {
      float o[4];
      gemv128<true, true>(o, sb + SM_F1, sb + SM_BA, warp, lane);
      float q0 = (t >> 1) ? o[2] : o[0], q1 = (t >> 1) ? o[3] : o[1];
      STAMP(30);
      uint32_t ra, rb;
      asm volatile("mapa.shared::cluster.u32 %0, %1, %2;" : "=r"(ra) : "r"(sb + SM_XQ + tid * 8), "r"(r ^ 1));
      asm volatile("mapa.shared::cluster.u32 %0, %1, %2;" : "=r"(rb) : "r"(BAR(B_XQ)), "r"(r ^ 1));
      asm volatile("st.async.weak.shared::cluster.mbarrier::complete_tx::bytes.v2.b32 [%0], {%1,%2}, [%3];"
                   ::"r"(ra), "r"(__float_as_uint(q0)), "r"(__float_as_uint(q1)), "r"(rb) : "memory");
      mbar_wait(BAR(B_XQ));
      const float2 pq = lds8f(sb + SM_XQ + tid * 8);
      q0 = __uint_as_float(__float_as_uint(q0 + pq.x) & ~M_F32);
      q1 = __uint_as_float(__float_as_uint(q1 + pq.y) & ~M_F32);
      st_rlx4(qpp, __float_as_uint(r ? q1 : q0) | tg2);
      STAMP_T(4, 0);
      pause(D_Q);
      const uint32_t* op = S->qpart + (((j >> 1) ^ 1) * 8 + warp) * 64 + lane;
      uint32_t u0, u1;
      int it = 0;
#pragma unroll 1
      while (true) {
        u0 = ld_rlx4(op); u1 = ld_rlx4(op + 32);
        if (!__any_sync(0xffffffffu, (((u0 ^ tg2) | (u1 ^ tg2)) & M_F32) != 0)) break;
        if (++it >= SPIN_LIMIT) { flag_err(3); break; }
      }
      const uint32_t qw = pack_bf16(q0 + __uint_as_float(u0 ^ tg2), q1 + __uint_as_float(u1 ^ tg2));
      const uint32_t a = sb + SM_BB + 2 * (t & 1) * 272 + (16 * warp + g + 8 * (t >> 1)) * 2;
      sts2(a, (uint16_t)qw);
      sts2(a + 272, (uint16_t)(qw >> 16));
    }
    STAMP_T(5, 0);
    if (warp == 7) mbar_wait_n<4>(BAR(I_WUK));
    bar_sync(1, 256);
    STAMP_T(6, 0);
    {
      float o[4];
      gemv128<false, true>(o, sb + SM_F2, sb + SM_BB, warp, lane);
      const float v0 = (t >> 1) ? o[2] : o[0], v1 = (t >> 1) ? o[3] : o[1];
      const float recv = __shfl_xor_sync(0xffffffffu, (g & 1) ? v0 : v1, 4);
      const float lo = (g & 1) ? recv : v0, hi = (g & 1) ? v1 : recv;
      uint32_t w = pack_bf16(lo, hi);
      const uint32_t lb = __float_as_uint(lo);
      const uint32_t w0 = (w & 0xFFFF0000u) | (((lb + 0xFFFFu + ((lb >> 17) & 1u)) >> 16) & 0xFFFEu) | par;
      const uint32_t w1 = __shfl_down_sync(0xffffffffu, w, 8), w2 = __shfl_down_sync(0xffffffffu, w, 16), w3 = __shfl_down_sync(0xffffffffu, w, 24);
      if (lane < 8) st_rlx128(qap, w0, w1, w2, w3);
      __syncwarp();
    }
    STAMP_T(7, 0);
    const int wword = ((g & 1) ? g + 7 : g) / 2;
    uint32_t* const ctp = S->ctxp + (j * 4 + t) * 64 + warp * 8 + wword;
    uint32_t* const otp = S->outp + ((t * 32 + 8 * qr + warp) * 32 + hd) * 8 + wword;
    uint32_t* const stp = S->stats + (((r * 32 + 8 * (warp & 3) + 2 * t + (g & 1)) * 4 + ab) * 16 + as) * 2;
    st_rlx4(ctp, ep ^ 1);
    st_rlx4(otp, ep ^ 1);
    if (j < 86) {
#pragma unroll
      for (int mt = 0; mt < 4; mt++) st_rlx4(S->yp + (((lane >> 3) * 32 + 4 * warp + mt) * 88 + j) * 8 + (lane & 7), ep ^ 1);
    }
    if (warp < 4 && lane < 8) st_rlx8(stp, make_uint2(ep ^ 1, ep ^ 1));
    {
      const uint32_t* base = S->qabs + (ab * 2 + r) * 4096 + tid * 4;
      const uint32_t* pp[4] = {base, base + 1024, base + 2048, base + 3072};
      uint4 v[4];
      while ((uint32_t)clock() - clk0 < S2_START) { }
      {
        uint32_t bad[4] = {1, 1, 1, 1};
        int it = 0;
#pragma unroll 1
        while (true) {
#pragma unroll
          for (int i = 0; i < 4; i++) ld_rlx128_if(v[i], pp[i], bad[i]);
#pragma unroll
          for (int i = 0; i < 4; i++) bad[i] = (v[i].x ^ par) & 1u;
          if (!__any_sync(0xffffffffu, (bad[0] | bad[1] | bad[2] | bad[3]) != 0)) break;
          if (++it >= SPIN_LIMIT) { flag_err(4); break; }
        }
      }
#pragma unroll
      for (int i = 0; i < 4; i++) sts16(sb + SM_Q + i * 4096 + tid * 16, make_uint4(v[i].x ^ par, v[i].y, v[i].z, v[i].w));
      fence_async_smem();
    }
    bar_sync(1, 256);
    STAMP_T(8, 0);

    if (warp < 4) {
      uint32_t mrun = 0xFF80FF80u;
      float lrun0 = 0.f, lrun1 = 0.f;
      constexpr float LOG2E = 1.4426950408889634f;
      {
        uint32_t* d0 = S->opart + ((size_t)((2 * r + (warp >> 1)) * 4 + ab) * 16 + as) * 64 + ((warp & 1) * 8 + g) * 4 + (size_t)(2 * t) * (4 * 4 * 16 * 64);
        const uint4 inv = make_uint4(par ^ 1, par ^ 1, par ^ 1, par ^ 1);
#pragma unroll 1
        for (int q = 0; q < 8; q++) st_rlx16(d0 + (size_t)(8 * (q >> 1) + (q & 1)) * (4 * 4 * 16 * 64), inv);
      }
#pragma unroll 1
      for (int tt = 0; tt < 4; tt++) {
        mbar_wait(BAR(B_XS + tt));
        uint32_t w[8];
#pragma unroll
        for (int i = 0; i < 4; i++) {
          const uint32_t o_ = warp * 2048 + (i * 32 + lane) * 16;
          const float4 v = lds16f(sb + SM_XS + tt * 8192 + o_), o = lds16f(sb + SM_XL + (tt == 3 ? 0 : tt) * 8192 + o_);
          const uint32_t u0 = pack_bf16(o.x + v.x, o.y + v.y), u1 = pack_bf16(o.z + v.z, o.w + v.w);
          w[2 * i] = pack_bf16(bf_lo(u0) * 0.08838834764831845f, bf_hi(u0) * 0.08838834764831845f);
          w[2 * i + 1] = pack_bf16(bf_lo(u1) * 0.08838834764831845f, bf_hi(u1) * 0.08838834764831845f);
        }
        if (tt == 3) STAMP(10);
        uint32_t mn = bf2_max(bf2_max(bf2_max(w[0], w[1]), bf2_max(w[2], w[3])), bf2_max(bf2_max(w[4], w[5]), bf2_max(w[6], w[7])));
        mn = bf2_max(mn, __shfl_xor_sync(0xffffffffu, mn, 4));
        mn = bf2_max(mn, __shfl_xor_sync(0xffffffffu, mn, 8));
        mn = bf2_max(bf2_max(mn, __shfl_xor_sync(0xffffffffu, mn, 16)), mrun);
        const float ml0 = bf_lo(mn) * LOG2E, ml1 = bf_hi(mn) * LOG2E;
        const float al0 = ex2(fmaf(bf_lo(mrun), LOG2E, -ml0)), al1 = ex2(fmaf(bf_hi(mrun), LOG2E, -ml1));
        mrun = mn;
        uint32_t pk[8];
        float p0 = 0.f, p1 = 0.f;
#pragma unroll
        for (int i = 0; i < 8; i++) {
          const float a = ex2(fmaf(bf_lo(w[i]), LOG2E, -ml0)), c = ex2(fmaf(bf_hi(w[i]), LOG2E, -ml1));
          p0 += a; p1 += c;
          pk[i] = pack_bf16(a, c);
        }
        lrun0 = fmaf(lrun0, al0, p0);
        lrun1 = fmaf(lrun1, al1, p1);
        {
          const int q = lane >> 3, rr = lane & 7;
          const uint32_t pb = sb + SM_P + (tt & 1) * 4096 + (8 * warp + rr) * 128;
          if (tt >= 2) mbar_wait(BAR(B_PVDONE + tt - 2));
          stsm4t(pb + ((q ^ rr) << 4), pk[0], pk[1], pk[2], pk[3]);
          stsm4t(pb + (((4 + q) ^ rr) << 4), pk[4], pk[5], pk[6], pk[7]);
          if (g == 0) sts8(sb + SM_ALPHA + tt * 128 + (8 * warp + 2 * t) * 4, __float_as_uint(al0), __float_as_uint(al1));
          __syncwarp();
        }
        fence_async_smem();
        bar_arrive(3 + tt, 256);
        STAMP(36 + tt);
      }
#pragma unroll
      for (int o_ = 4; o_ < 32; o_ <<= 1) {
        lrun0 += __shfl_xor_sync(0xffffffffu, lrun0, o_);
        lrun1 += __shfl_xor_sync(0xffffffffu, lrun1, o_);
      }
      const uint32_t mw = g ? (mrun & 0xFFFF0000u) : (mrun << 16);
      if (lane < 8) st_rlx8(stp, make_uint2(mw | tg2, (__float_as_uint(g ? lrun1 : lrun0) & ~M_F32) | tg2));
      __syncwarp();
      STAMP(13);
      bar_sync(7, 256);
    } else {
      float o[4][16];
#pragma unroll
      for (int x = 0; x < 4; x++)
#pragma unroll
        for (int i = 0; i < 16; i++) o[x][i] = 0.f;
      const int w = warp - 4, wt = tid - 128;
      uint32_t rslot, rbar;
      asm volatile("mapa.shared::cluster.u32 %0, %1, %2;" : "=r"(rslot) : "r"(sb + SM_XS), "r"(r ^ 1));
      asm volatile("mapa.shared::cluster.u32 %0, %1, %2;" : "=r"(rbar) : "r"(BAR(B_XS)), "r"(r ^ 1));
      int uq = 0, up = 0;
#pragma unroll 1
      for (int step = 0; step < 8; step++) {
        if ((0x1B >> step) & 1) {
          float s[16];
#pragma unroll
          for (int i = 0; i < 16; i++) s[i] = 0.f;
#pragma unroll
          for (int x = 0; x < 4; x++) {
            mbar_wait(BAR(I_CKV + uq * 4 + x));
            const uint64_t da = gdesc(sb + SM_K + uq * 32768 + x * 8192), db = gdesc(sb + SM_Q + x * 4096);
            wg_fence();
#pragma unroll
            for (int kk = 0; kk < 4; kk++) wgmma_n32<0>(s, da + kk * 2, db + kk * 2, (x | kk) != 0);
            wg_commit();
          }
          wg_wait0();
          STAMP(32 + uq);
          if (uq == 3) {
#pragma unroll
            for (int i = 0; i < 4; i++)
              asm volatile("st.async.weak.shared::cluster.mbarrier::complete_tx::bytes.v4.b32 [%0], {%1,%2,%3,%4}, [%5];"
                           ::"r"(rslot + 3 * 8192 + i * 2048 + wt * 16), "r"(__float_as_uint(s[4 * i])), "r"(__float_as_uint(s[4 * i + 1])),
                             "r"(__float_as_uint(s[4 * i + 2])), "r"(__float_as_uint(s[4 * i + 3])), "r"(rbar + 3 * 8) : "memory");
          }
#pragma unroll
          for (int i = 0; i < 4; i++)
            sts16(sb + SM_XL + (uq == 3 ? 0 : uq) * 8192 + i * 2048 + wt * 16,
                  make_uint4(__float_as_uint(s[4 * i]), __float_as_uint(s[4 * i + 1]), __float_as_uint(s[4 * i + 2]), __float_as_uint(s[4 * i + 3])));
          if (uq != 3) fence_async_smem();
          bar_sync(8, 128);
          if (wt == 0) {
            if (uq != 3) {
              asm volatile("cp.async.bulk.shared::cluster.shared::cta.mbarrier::complete_tx::bytes [%0], [%1], 8192, [%2];"
                           ::"r"(rslot + uq * 8192), "r"(sb + SM_XL + uq * 8192), "r"(rbar + uq * 8) : "memory");
              asm volatile("cp.async.bulk.commit_group;" ::: "memory");
            }
            mbar_arrive(BAR(B_XS + uq));
          }
          __syncwarp();
          uq++;
        } else {
          if (wt == 0 && up == 0) asm volatile("cp.async.bulk.wait_group.read 0;" ::: "memory");
          __syncwarp();
          bar_sync(3 + up, 256);
#pragma unroll
          for (int jj = 0; jj < 4; jj++) {
            const float2 a = lds8f(sb + SM_ALPHA + up * 128 + (8 * jj + 2 * t) * 4);
#pragma unroll
            for (int x = 0; x < 4; x++) {
              o[x][4 * jj] *= a.x; o[x][4 * jj + 1] *= a.y; o[x][4 * jj + 2] *= a.x; o[x][4 * jj + 3] *= a.y;
            }
          }
          wg_fence();
#pragma unroll
          for (int kt = 0; kt < 4; kt++) {
            const uint64_t db = gdesc(sb + SM_P + (up & 1) * 4096) + kt * 2;
#pragma unroll
            for (int x = 0; x < 4; x++) wgmma_n32<1>(o[x], gdesc(sb + SM_K + up * 32768 + x * 8192 + kt * 2048), db, 1);
          }
          wg_commit();
          wg_wait0();
          if (lane == 0) mbar_arrive(BAR(B_PVDONE + up));
          STAMP(40 + up);
          up++;
        }
      }
      uint32_t* dst0 = S->opart + ((size_t)((2 * r + (w >> 1)) * 4 + ab) * 16 + as) * 64 + ((w & 1) * 8 + g) * 4;
#pragma unroll
      for (int jj = 0; jj < 4; jj++) {
#pragma unroll
        for (int e = 0; e < 2; e++) {
          const int head = 8 * jj + 2 * t + e;
          uint4 v;
          v.x = (pack_bf16(o[0][4 * jj + e], o[0][4 * jj + 2 + e]) & ~1u) | par;
          v.y = (pack_bf16(o[1][4 * jj + e], o[1][4 * jj + 2 + e]) & ~1u) | par;
          v.z = (pack_bf16(o[2][4 * jj + e], o[2][4 * jj + 2 + e]) & ~1u) | par;
          v.w = (pack_bf16(o[3][4 * jj + e], o[3][4 * jj + 2 + e]) & ~1u) | par;
          st_rlx16(dst0 + (size_t)head * (4 * 4 * 16 * 64), v);
        }
      }
      bar_arrive(7, 256);
      STAMP(12);
    }

    {
      const int b = warp >> 1, sh = warp & 1, ch = lane & 15, sl = lane >> 4;
      if (warp == 3) mbar_wait_n<4>(BAR(I_WUV));
      const uint32_t* base = S->opart + ((size_t)((hd * 4 + qr) * 4 + b) * 16 + 8 * sh + sl) * 64 + ch * 4;
      const uint32_t* pp[4] = {base, base + 128, base + 256, base + 384};
      uint4 v[4];
      const uint32_t* sp = S->stats + ((((qr >> 1) * 32 + hd) * 4 + b) * 16 + (lane & 15)) * 2;
      pause(D_O);
#pragma unroll
      for (int i = 0; i < 4; i++) v[i] = ld_rlx16(pp[i]);
      uint2 st;
      {
        int it = 0;
#pragma unroll 1
        while (true) {
          st = ld_rlx8(sp);
          if (!__any_sync(0xffffffffu, (((st.x ^ tg2) | (st.y ^ tg2)) & M_F32) != 0)) break;
          if (++it >= SPIN_LIMIT) { flag_err(5); break; }
        }
        __syncwarp();
      }
      STAMP(22);
      const float m = __uint_as_float(st.x ^ tg2), l = __uint_as_float(st.y ^ tg2);
      float M = m;
#pragma unroll
      for (int o_ = 1; o_ < 16; o_ <<= 1) M = fmaxf(M, __shfl_xor_sync(0xffffffffu, M, o_));
      const float e = ex2((m - M) * 1.4426950408889634f);
      float L = e * l;
#pragma unroll
      for (int o_ = 1; o_ < 16; o_ <<= 1) L += __shfl_xor_sync(0xffffffffu, L, o_);
      const float wgt = __fdividef(e, L);
      poll16<4, false>(pp, v, par, M_PAR, 6);
      __syncwarp();
      STAMP(23);
      float acc[8];
#pragma unroll
      for (int i = 0; i < 8; i++) acc[i] = 0.f;
#pragma unroll
      for (int i = 0; i < 4; i++) {
        const float wi = __shfl_sync(0xffffffffu, wgt, 8 * sh + 2 * i + sl);
        const uint32_t w4[4] = {v[i].x, v[i].y, v[i].z, v[i].w};
#pragma unroll
        for (int k = 0; k < 4; k++) {
          acc[2 * k] = fmaf(wi, bf_lo(w4[k] ^ par), acc[2 * k]);
          acc[2 * k + 1] = fmaf(wi, bf_hi(w4[k]), acc[2 * k + 1]);
        }
      }
      float rs[4];
#pragma unroll
      for (int k = 0; k < 4; k++) {
        const float keep = sl ? acc[k + 4] : acc[k], send = sl ? acc[k] : acc[k + 4];
        rs[k] = keep + __shfl_xor_sync(0xffffffffu, send, 16);
      }
      const uint32_t rowb = sb + SM_BA + warp * 272 + (64 * sl + 16 * (ch >> 3) + (ch & 7)) * 2;
#pragma unroll
      for (int k = 0; k < 4; k++) sts2(rowb + ((k >> 1) * 32 + (k & 1) * 8) * 2, (uint16_t)(pack_bf16(rs[k], 0.f) & 0xFFFFu));
    }
    STAMP_T(14, 0);
    bar_sync(1, 256);
    STAMP_T(15, 0);
    {
      float o[4];
      gemv128<true, false>(o, sb + SM_WUV, sb + SM_BA, warp, lane);
      const float v0 = o[0] + o[1], v1 = o[2] + o[3];
      const float recv = __shfl_xor_sync(0xffffffffu, (g & 1) ? v0 : v1, 4);
      const uint32_t w = (g & 1) ? pack_bf16(recv, v1) : pack_bf16(v0, recv);
      st_rlx4(ctp, (w & ~1u) | par);
    }
    STAMP(28);
    if (warp == 7) mbar_wait_n<4>(BAR(I_WO));
    {
      const int b = warp >> 1, cq = 2 * (warp & 1) + (lane >> 4), ch = lane & 15, sl = lane >> 4;
      pause(D_CTX);
      const uint32_t* pp[1] = {S->ctxp + ((hd * 4 + cq) * 4 + b) * 64 + ch * 4};
      uint4 v[1];
      poll16<1>(pp, v, par, M_PAR, 7);
      __syncwarp();
      const float f[8] = {bf_lo(v[0].x ^ par), bf_hi(v[0].x), bf_lo(v[0].y ^ par), bf_hi(v[0].y),
                          bf_lo(v[0].z ^ par), bf_hi(v[0].z), bf_lo(v[0].w ^ par), bf_hi(v[0].w)};
      float rs[4];
#pragma unroll
      for (int k = 0; k < 4; k++) {
        const float keep = sl ? f[k + 4] : f[k], send = sl ? f[k] : f[k + 4];
        rs[k] = keep + __shfl_xor_sync(0xffffffffu, send, 16);
      }
      sts8(sb + SM_BB + warp * 272 + (8 * ch + 4 * sl) * 2, pack_bf16(rs[0], rs[1]), pack_bf16(rs[2], rs[3]));
    }
    uint4 mv[8];
    const uint32_t* const mvp = S->mod + (warp & 3) * 3072 + 1536 + lane * 4;
    if (j < 86 && warp < 4) {
#pragma unroll
      for (int i = 0; i < 8; i++) mv[i] = ld_rlx16(mvp + i * 128);
    }
    STAMP_T(16, 0);
    bar_sync(1, 256);
    {
      float o[4];
      gemv128<true, false>(o, sb + SM_WO, sb + SM_BB, warp, lane);
      const float v0 = o[0] + o[1], v1 = o[2] + o[3];
      const float recv = __shfl_xor_sync(0xffffffffu, (g & 1) ? v0 : v1, 4);
      const uint32_t w = (g & 1) ? pack_bf16(recv, v1) : pack_bf16(v0, recv);
      st_rlx4(otp, (w & ~1u) | par);
      if (lane == 0) mbar_arrive(BAR(B_OUTP));
      __syncwarp();
    }
    STAMP_T(17, 0);
    if (j < 86) {
      if (warp < 4) {
        uint32_t sh[8], sc[8], xw[8];
        {
          const uint32_t* pp[8] = {mvp, mvp + 128, mvp + 256, mvp + 384, mvp + 512, mvp + 640, mvp + 768, mvp + 896};
          poll16<8, false>(pp, mv, ep, M_T16, 8);
          __syncwarp();
#pragma unroll
          for (int i = 0; i < 4; i++) {
            sh[2 * i] = hi2(mv[i].x, mv[i].y); sh[2 * i + 1] = hi2(mv[i].z, mv[i].w);
            sc[2 * i] = hi2(mv[4 + i].x, mv[4 + i].y); sc[2 * i + 1] = hi2(mv[4 + i].z, mv[4 + i].w);
          }
        }
        mbar_wait(BAR(B_X1));
        pause(D_X1);
        {
          const uint32_t* xp = S->x1 + warp * 256 + lane * 2;
          int it = 0;
#pragma unroll 1
          while (true) {
            uint32_t bad = 0;
#pragma unroll
            for (int i = 0; i < 4; i++) { const uint2 v = ld_rlx8(xp + i * 64); xw[2 * i] = v.x ^ par; xw[2 * i + 1] = v.y ^ par; }
#pragma unroll
            for (int i = 0; i < 8; i++) bad |= xw[i];
            if (!__any_sync(0xffffffffu, (bad & M_PAR) != 0)) break;
            if (++it >= SPIN_LIMIT) { flag_err(9); break; }
          }
        }
        __syncwarp();
        STAMP(20);
        ln_row(xw);
        STAMP(21);
        const uint32_t a = sb + SM_BH2 + warp * 1040 + lane * 8;
#pragma unroll
        for (int i = 0; i < 4; i++) sts8(a + i * 256, modulate(xw[2 * i], sc[2 * i], sh[2 * i]), modulate(xw[2 * i + 1], sc[2 * i + 1], sh[2 * i + 1]));
      }
      if (warp == 7) { mbar_wait_n<2>(BAR(I_W1)); mbar_wait_n<2>(BAR(I_W2)); }
      bar_sync(1, 256);
      STAMP_T(18, 0);
      {
        float o[4];
        gemv_narrow<2>(o, sb + SM_W1 + warp * 64 * 32, sb + SM_BH2 + warp * 64 * 2, lane);
        const int row = g + 8 * (t >> 1), b0 = 2 * (t & 1);
        const uint32_t ra = sb + SM_RED + row * 144 + (warp >> 2) * 64 + b0 * 16 + (warp & 3) * 4;
        sts4f(ra, (t >> 1) ? o[2] : o[0]);
        sts4f(ra + 16, (t >> 1) ? o[3] : o[1]);
      }
      bar_sync(1, 256);
      STAMP(31);
      {
        float hv[4];
#pragma unroll
        for (int i = 0; i < 4; i++) {
          const int f = 2 * t + (i & 1) + 8 * (i >> 1);
          const uint32_t a = sb + SM_RED + f * 144 + (g & 3) * 16;
          const float4 u = lds16f(a), w = lds16f(a + 64);
          hv[i] = fmaxf(((u.x + u.y) + (u.z + u.w)) + ((w.x + w.y) + (w.z + w.w)), 0.f);
        }
        const uint32_t b0 = pack_bf16(hv[0], hv[1]), b1 = pack_bf16(hv[2], hv[3]);
        const int ro = (lane & 7) + 8 * (lane >> 4);
        const int b = 2 * (t & 1) + (g & 1), row = (g + 8 * (t >> 1)) & ~1;
        uint32_t* dst = S->yp + ((b * 32 + 4 * warp) * 88 + j) * 8 + row / 2;
#pragma unroll
        for (int mt = 0; mt < 4; mt++) {
          uint32_t fa[4];
          ldsm4t(sb + SM_W2 + warp * 2048 + ro * 128 + (((2 * mt + ((lane >> 3) & 1)) ^ (lane & 7)) << 4), fa);
          float o[4] = {0.f, 0.f, 0.f, 0.f};
          mma16816(o, fa, b0, b1);
          const float v0 = (t >> 1) ? o[2] : o[0], v1 = (t >> 1) ? o[3] : o[1];
          const float recv = __shfl_xor_sync(0xffffffffu, (g & 1) ? v0 : v1, 4);
          const uint32_t w = (g & 1) ? pack_bf16(recv, v1) : pack_bf16(v0, recv);
          st_rlx4(dst + mt * 88 * 8, (w & ~1u) | par);
        }
        if (lane == 0) mbar_arrive(BAR(B_YP));
      }
      STAMP_T(19, 0);
    }
  }
}

}

typedef CUresult (*PFN_tmapEncodeTiled)(CUtensorMap*, CUtensorMapDataType, cuuint32_t, void*, const cuuint64_t*, const cuuint64_t*,
                                        const cuuint32_t*, const cuuint32_t*, CUtensorMapInterleave, CUtensorMapSwizzle,
                                        CUtensorMapL2promotion, CUtensorMapFloatOOBfill);

static void make_map(PFN_tmapEncodeTiled enc, CUtensorMap* m, const void* base, uint64_t cols, uint64_t rows, uint32_t boxc, uint32_t boxr) {
  cuuint64_t dims[2] = {cols, rows};
  cuuint64_t strides[1] = {cols * 2};
  cuuint32_t box[2] = {boxc, boxr};
  cuuint32_t es[2] = {1, 1};
  enc(m, CU_TENSOR_MAP_DATA_TYPE_BFLOAT16, 2, const_cast<void*>(base), dims, strides, box, es, CU_TENSOR_MAP_INTERLEAVE_NONE,
      boxc == 16 ? CU_TENSOR_MAP_SWIZZLE_32B : CU_TENSOR_MAP_SWIZZLE_128B, CU_TENSOR_MAP_L2_PROMOTION_L2_128B,
      CU_TENSOR_MAP_FLOAT_OOB_FILL_NONE);
}

extern "C" void kernel_launch(void* const* d_in, const int* in_sizes, int n_in, void* d_out, int out_size) {
  (void)in_sizes; (void)n_in; (void)out_size;
  static PFN_tmapEncodeTiled enc = nullptr;
  static mla::Scratch* scr = nullptr;
  if (!enc) {
    void* fn = nullptr;
    cudaDriverEntryPointQueryResult qr;
    cudaGetDriverEntryPoint("cuTensorMapEncodeTiled", &fn, cudaEnableDefault, &qr);
    enc = (PFN_tmapEncodeTiled)fn;
    cudaFuncSetAttribute(mla::decode_kernel, cudaFuncAttributeMaxDynamicSharedMemorySize, (int)mla::SMEM_BYTES);
    cudaGetSymbolAddress((void**)&scr, mla::g_scr);
  }
  mla::Params p;
  make_map(enc, &p.wq, d_in[2], 4096, 512, 64, 64);
  make_map(enc, &p.wuk, d_in[3], 4096, 512, 64, 64);
  make_map(enc, &p.ckv, d_in[1], 512, 16384, 64, 64);
  make_map(enc, &p.wmod, d_in[10], 3072, 512, 16, 256);
  make_map(enc, &p.wuv, d_in[4], 4096, 512, 64, 32);
  make_map(enc, &p.wo, d_in[5], 512, 4096, 64, 64);
  make_map(enc, &p.w1, d_in[7], 1376, 512, 16, 256);
  make_map(enc, &p.w2, d_in[8], 512, 1376, 64, 16);
  p.x = (const __nv_bfloat16*)d_in[0];
  p.c = (const __nv_bfloat16*)d_in[9];
  p.wmod_ptr = (const __nv_bfloat16*)d_in[10];
  p.out = (__nv_bfloat16*)d_out;
  p.scr = scr;
  mla::decode_kernel<<<mla::NCTA, mla::NTHR, mla::SMEM_BYTES, cudaStreamPerThread>>>(p);
}
```
